```python
import torch

def _softmax(x, axis=-1):
    return torch.softmax(x, dim=axis)
def _gelu(x):
    return torch.nn.functional.gelu(x, approximate="tanh")
def _silu(x):
    return torch.nn.functional.silu(x)
def _sigmoid(x):
    return torch.sigmoid(x)
def _layernorm(x, axis=-1, eps=1e-5):
    m = x.mean(dim=axis, keepdim=True)
    v = x.var(dim=axis, keepdim=True, unbiased=False)
    return (x - m) / torch.sqrt(v + eps)
def _scatter_add(tgt, idx, src, axis=0):
    return tgt.clone().index_add_(axis, idx, src)
def _segment_sum(src, seg, n):
    out = torch.zeros((n,) + src.shape[1:], dtype=src.dtype)
    return out.index_add_(0, seg, src)
def _pad(x, pw):
    flat = tuple(v for pair in reversed(pw) for v in pair)
    return torch.nn.functional.pad(x, flat)

kernel_name = 'gated_mix__ssm_conv_s4__moe_arch_mod__prompt'

def setup_inputs():

    _w = (lambda a: (lambda t: t.to(torch.bfloat16) if t.is_floating_point() else t)(torch.as_tensor(a)))
    def _A_setup():
        B, L, D, N = 1, 2048, 576, 128
        A_re = -(lambda _x: torch.exp(torch.as_tensor(_x)))((lambda *s: torch.randn(*s, dtype=torch.bfloat16) * 3.2)(D, N))
        A_im = torch.pi * (lambda *s: torch.randn(*s, dtype=torch.bfloat16) * 0.05)(D, N)
        B_re = (lambda *s: torch.randn(*s, dtype=torch.bfloat16) * 0.2)(D, N)
        B_im = (lambda *s: torch.randn(*s, dtype=torch.bfloat16) * 0.2)(D, N)
        C_re = (lambda *s: torch.randn(*s, dtype=torch.bfloat16) * 0.2)(D, N)
        C_im = (lambda *s: torch.randn(*s, dtype=torch.bfloat16) * 0.2)(D, N)
        log_dt = (lambda *s: torch.randn(*s, dtype=torch.bfloat16) * 0.05)(D) * 0.5 - 4.0
        Dskip = (lambda *s: torch.randn(*s, dtype=torch.bfloat16) * 0.1)(D)
        return {
            "u": _w((lambda *s: torch.randn(*s, dtype=torch.bfloat16) * 0.05)(B, L, D)),
            "A_re": _w(A_re),
            "A_im": _w(A_im),
            "B_re": _w(B_re),
            "B_im": _w(B_im),
            "C_re": _w(C_re),
            "C_im": _w(C_im),
            "log_dt": _w(log_dt),
            "Dskip": _w(Dskip),
        }
    _A_in = _A_setup()

    def _B_setup():
        B, S, D, F, C = 1, 2048, 576, 4608, 8
        return {
            "x": _w((lambda *s: torch.randn(*s, dtype=torch.bfloat16) * 0.05)(B, S, D)),
            "w_r": _w((lambda *s: torch.randn(*s, dtype=torch.bfloat16) * 3.2)(D)),
            "w_gate": _w((lambda *s: torch.randn(*s, dtype=torch.bfloat16) * 0.1)(D, F)),
            "w_up": _w((lambda *s: torch.randn(*s, dtype=torch.bfloat16) * 0.1)(D, F)),
            "w_down": _w((lambda *s: torch.randn(*s, dtype=torch.bfloat16) * 0.1)(F, D)),
        }
    _B_in = _B_setup()

    return {
        "A_u": _A_in["u"],
        "A_A_re": _A_in["A_re"],
        "A_A_im": _A_in["A_im"],
        "A_B_re": _A_in["B_re"],
        "A_B_im": _A_in["B_im"],
        "A_C_re": _A_in["C_re"],
        "A_C_im": _A_in["C_im"],
        "A_log_dt": _A_in["log_dt"],
        "A_Dskip": _A_in["Dskip"],
        "B_x": _B_in["x"],
        "B_w_r": _B_in["w_r"],
        "B_w_gate": _B_in["w_gate"],
        "B_w_up": _B_in["w_up"],
        "B_w_down": _B_in["w_down"],
        "gate_w": _w((lambda *s: torch.randn(*s, dtype=torch.bfloat16) * 0.05)(576) * 16.0),
    }

def reference(A_u, A_A_re, A_A_im, A_B_re, A_B_im, A_C_re, A_C_im, A_log_dt, A_Dskip, B_x, B_w_r, B_w_gate, B_w_up, B_w_down, gate_w):
    def _A_ref(u, A_re, A_im, B_re, B_im, C_re, C_im, log_dt, Dskip):
        Bsz, L, D = u.shape
        dt = torch.exp(log_dt)[:, None]
        A = A_re + 1j * A_im
        Bc = B_re + 1j * B_im
        Cc = C_re + 1j * C_im
        logdA = dt * A
        dB = dt * Bc
        l = (lambda x, dt: x.to(dt))(torch.arange(L), A_re.dtype)
        P = torch.exp(logdA[:, :, None] * l[None, None, :])
        K = torch.einsum("dn,dnl,dn->dl", Cc, P, dB).real
        L2 = 2 * L
        Kp = _pad(K, ((0, 0), (0, L)))
        up = (lambda x, *d: x.permute(*d))(u, 0, 2, 1)
        up = _pad(up, ((0, 0), (0, 0), (0, L)))
        Kf = (lambda x, axes=(-2,-1): torch.fft.rfft2(x.float(), dim=axes))(Kp[:, None, :], axes=(-2, -1))
        Uf = (lambda x, axes=(-2,-1): torch.fft.rfft2(x.float(), dim=axes))(up[:, :, None, :], axes=(-2, -1))
        Yf = Uf * Kf[None, :, :, :]
        y = (lambda x, s, axes=(-2,-1): torch.fft.irfft2(x, s=s, dim=axes).to(torch.bfloat16))(Yf, (1, L2), axes=(-2, -1))[:, :, 0, :L]
        y = (lambda x, *d: x.permute(*d))(y, 0, 2, 1) + u * Dskip[None, None, :]
        return y

    def _B_ref(x, w_r, w_gate, w_up, w_down):
        B, S, D = x.shape
        C = 8
        r = x @ w_r
        idx = torch.argsort(-r, axis=-1)[:, :C]
        idx_e = (lambda x, n, axis: torch.repeat_interleave(x, n, dim=axis))(idx.reshape(B, C, 1), D, axis=2)
        x_sel = (lambda x, i, axis: torch.take_along_dim(x, i, dim=axis))(x, idx_e, axis=1)
        g = _silu(x_sel @ w_gate)
        u = x_sel @ w_up
        y = (g * u) @ w_down
        r_sel = _sigmoid((lambda x, i, axis: torch.take_along_dim(x, i, dim=axis))(r, idx, axis=1))
        y = y * r_sel.reshape(B, C, 1)
        b_off = (torch.arange(B) * S).reshape(B, 1)
        flat_idx = (idx + b_off).reshape(B * C)
        zero = (x * 0.0).reshape(B * S, D)
        upd = _scatter_add(zero, flat_idx, y.reshape(B * C, D), axis=0)
        return x + upd.reshape(B, S, D)

    x = A_u
    g = _sigmoid((x * gate_w).sum(-1, keepdims=True))
    a = _A_ref(x, A_A_re, A_A_im, A_B_re, A_B_im, A_C_re, A_C_im, A_log_dt, A_Dskip)
    b = _B_ref(x, B_w_r, B_w_gate, B_w_up, B_w_down)
    return g * a + (1 - g) * b
```

```cpp
#include <cuda_runtime.h>
#include <cuda_bf16.h>
#include <cuda_fp16.h>
#include <cuda.h>
#include <stdint.h>

#define RDELAY 1000
#define UDELAY 0
#define WDELAY 1800
#define WWIN 4

namespace {

constexpr int L_SEQ = 2048, DM = 576, NST = 128, FF = 4608;
constexpr int NCTA = 132, NFFN = 60, FFN0 = 8, NTHR = 384;

struct Scratch {
    unsigned launch; unsigned pad0[31];
    uint32_t sel[32];
    uint32_t rec[L_SEQ];
    uint4 part[36 * NFFN * 32];
};
__device__ Scratch g_scr;

struct Params {
    const __nv_bfloat16 *Are, *Aim, *Bre, *Bim, *Cre, *Cim, *logdt, *Dskip, *u, *wr, *gatew;
    __nv_bfloat16* out;
    Scratch* scr;
};

#define TSTAMP(i)

__device__ __forceinline__ uint32_t smem_u32(const void* p) { return (uint32_t)__cvta_generic_to_shared(p); }
__device__ __forceinline__ uint32_t pack_bf16(float lo, float hi) { uint32_t r; asm("cvt.rn.bf16x2.f32 %0, %1, %2;" : "=r"(r) : "f"(hi), "f"(lo)); return r; }
__device__ __forceinline__ uint32_t pack_f16(float lo, float hi) { uint32_t r; asm("cvt.rn.f16x2.f32 %0, %1, %2;" : "=r"(r) : "f"(hi), "f"(lo)); return r; }
__device__ __forceinline__ float bf_lo(uint32_t w) { return __uint_as_float(w << 16); }
__device__ __forceinline__ float bf_hi(uint32_t w) { return __uint_as_float(w & 0xffff0000u); }
__device__ __forceinline__ float rbf(float x) { return bf_lo(pack_bf16(x, 0.f)); }
__device__ __forceinline__ uint32_t hmul2(uint32_t a, uint32_t b) { __nv_bfloat162 r = __hmul2_rn(*(__nv_bfloat162*)&a, *(__nv_bfloat162*)&b); return *(uint32_t*)&r; }
__device__ __forceinline__ uint32_t hadd2(uint32_t a, uint32_t b) { __nv_bfloat162 r = __hadd2_rn(*(__nv_bfloat162*)&a, *(__nv_bfloat162*)&b); return *(uint32_t*)&r; }
__device__ __forceinline__ uint32_t hsub2(uint32_t a, uint32_t b) { __nv_bfloat162 r = __hsub2_rn(*(__nv_bfloat162*)&a, *(__nv_bfloat162*)&b); return *(uint32_t*)&r; }
__device__ __forceinline__ void mma_bf(float (&c)[4], uint32_t a0, uint32_t a1, uint32_t a2, uint32_t a3, uint32_t b0, uint32_t b1) {
    asm("mma.sync.aligned.m16n8k16.row.col.f32.bf16.bf16.f32 {%0,%1,%2,%3}, {%4,%5,%6,%7}, {%8,%9}, {%0,%1,%2,%3};"
        : "+f"(c[0]), "+f"(c[1]), "+f"(c[2]), "+f"(c[3]) : "r"(a0), "r"(a1), "r"(a2), "r"(a3), "r"(b0), "r"(b1));
}
__device__ __forceinline__ void mma_bf0(float (&c)[4], uint32_t a0, uint32_t a1, uint32_t a2, uint32_t a3, uint32_t b0, uint32_t b1) {
    asm("mma.sync.aligned.m16n8k16.row.col.f32.bf16.bf16.f32 {%0,%1,%2,%3}, {%4,%5,%6,%7}, {%8,%9}, {%10,%10,%10,%10};"
        : "=f"(c[0]), "=f"(c[1]), "=f"(c[2]), "=f"(c[3]) : "r"(a0), "r"(a1), "r"(a2), "r"(a3), "r"(b0), "r"(b1), "f"(0.f));
}
__device__ __forceinline__ void mma_bf8(float (&c)[4], uint32_t a0, uint32_t a1, uint32_t b0) {
    asm("mma.sync.aligned.m16n8k8.row.col.f32.bf16.bf16.f32 {%0,%1,%2,%3}, {%4,%5}, {%6}, {%0,%1,%2,%3};"
        : "+f"(c[0]), "+f"(c[1]), "+f"(c[2]), "+f"(c[3]) : "r"(a0), "r"(a1), "r"(b0));
}
__device__ __forceinline__ void mma_f16(float (&c)[4], uint32_t a0, uint32_t a1, uint32_t a2, uint32_t a3, uint32_t b0, uint32_t b1) {
    asm("mma.sync.aligned.m16n8k16.row.col.f32.f16.f16.f32 {%0,%1,%2,%3}, {%4,%5,%6,%7}, {%8,%9}, {%0,%1,%2,%3};"
        : "+f"(c[0]), "+f"(c[1]), "+f"(c[2]), "+f"(c[3]) : "r"(a0), "r"(a1), "r"(a2), "r"(a3), "r"(b0), "r"(b1));
}
__device__ __forceinline__ uint32_t lds16(uint32_t a) { uint32_t v; asm volatile("ld.shared.u16 %0, [%1];" : "=r"(v) : "r"(a)); return v; }
__device__ __forceinline__ uint32_t lds8(uint32_t a) { uint32_t v; asm volatile("ld.shared.u8 %0, [%1];" : "=r"(v) : "r"(a)); return v; }
__device__ __forceinline__ uint32_t lds32(uint32_t a) { uint32_t v; asm volatile("ld.shared.u32 %0, [%1];" : "=r"(v) : "r"(a)); return v; }
__device__ __forceinline__ uint2 lds64(uint32_t a) { uint2 v; asm volatile("ld.shared.v2.u32 {%0,%1}, [%2];" : "=r"(v.x), "=r"(v.y) : "r"(a)); return v; }
__device__ __forceinline__ uint4 lds128(uint32_t a) { uint4 v; asm volatile("ld.shared.v4.u32 {%0,%1,%2,%3}, [%4];" : "=r"(v.x), "=r"(v.y), "=r"(v.z), "=r"(v.w) : "r"(a)); return v; }
__device__ __forceinline__ void ldsm4(uint32_t (&r)[4], uint32_t a) {
    asm volatile("ldmatrix.sync.aligned.m8n8.x4.shared.b16 {%0,%1,%2,%3}, [%4];" : "=r"(r[0]), "=r"(r[1]), "=r"(r[2]), "=r"(r[3]) : "r"(a));
}
__device__ __forceinline__ void ldsm4t(uint32_t (&r)[4], uint32_t a) {
    asm volatile("ldmatrix.sync.aligned.m8n8.x4.trans.shared.b16 {%0,%1,%2,%3}, [%4];" : "=r"(r[0]), "=r"(r[1]), "=r"(r[2]), "=r"(r[3]) : "r"(a));
}
__device__ __forceinline__ void sts16(uint32_t a, uint32_t v) { asm volatile("st.shared.u16 [%0], %1;" :: "r"(a), "h"((unsigned short)v) : "memory"); }
__device__ __forceinline__ void sts32(uint32_t a, uint32_t v) { asm volatile("st.shared.u32 [%0], %1;" :: "r"(a), "r"(v) : "memory"); }
__device__ __forceinline__ void sts64(uint32_t a, uint32_t x, uint32_t y) { asm volatile("st.shared.v2.u32 [%0], {%1,%2};" :: "r"(a), "r"(x), "r"(y) : "memory"); }
__device__ __forceinline__ void sts128(uint32_t a, uint32_t x, uint32_t y, uint32_t z, uint32_t w) {
    asm volatile("st.shared.v4.u32 [%0], {%1,%2,%3,%4};" :: "r"(a), "r"(x), "r"(y), "r"(z), "r"(w) : "memory");
}
__device__ __forceinline__ void stsm4t(uint32_t a, uint32_t r0, uint32_t r1, uint32_t r2, uint32_t r3) {
    asm volatile("stmatrix.sync.aligned.m8n8.x4.trans.shared.b16 [%0], {%1,%2,%3,%4};" :: "r"(a), "r"(r0), "r"(r1), "r"(r2), "r"(r3) : "memory");
}
__device__ __forceinline__ void st_async64(uint32_t a, uint32_t x, uint32_t y, uint32_t bar) {
    asm volatile("st.async.weak.shared::cluster.mbarrier::complete_tx::bytes.v2.b32 [%0], {%1,%2}, [%3];" :: "r"(a), "r"(x), "r"(y), "r"(bar) : "memory");
}
__device__ __forceinline__ void st_async128(uint32_t a, uint32_t x, uint32_t y, uint32_t z, uint32_t w, uint32_t bar) {
    asm volatile("st.async.weak.shared::cluster.mbarrier::complete_tx::bytes.v4.b32 [%0], {%1,%2,%3,%4}, [%5];" :: "r"(a), "r"(x), "r"(y), "r"(z), "r"(w), "r"(bar) : "memory");
}
__device__ __forceinline__ void mbar_init(uint32_t b, uint32_t cnt) { asm volatile("mbarrier.init.shared::cta.b64 [%0], %1;" :: "r"(b), "r"(cnt) : "memory"); }
__device__ __forceinline__ void mbar_fence_init() { asm volatile("fence.mbarrier_init.release.cluster;" ::: "memory"); }
__device__ __forceinline__ void mbar_expect(uint32_t b, uint32_t bytes) { asm volatile("mbarrier.arrive.expect_tx.shared::cta.b64 _, [%0], %1;" :: "r"(b), "r"(bytes) : "memory"); }
__device__ __forceinline__ void mbar_arrive(uint32_t b) { asm volatile("mbarrier.arrive.shared::cta.b64 _, [%0];" :: "r"(b) : "memory"); }
__device__ __forceinline__ void mbar_wait(uint32_t b) {
    asm volatile("{ .reg .pred p; .reg .u32 n; mov.u32 n, 0;\n"
                 "W: mbarrier.try_wait.parity.shared::cta.b64 p, [%0], 0; @p bra D; add.u32 n, n, 1; setp.lt.u32 p, n, 4000000; @p bra W; trap;\n"
                 "D: }" :: "r"(b) : "memory");
}
__device__ __forceinline__ void mbar_wait_cluster(uint32_t b) {
    asm volatile("{ .reg .pred p; .reg .u32 n; mov.u32 n, 0;\n"
                 "W: mbarrier.try_wait.parity.acquire.cluster.shared::cta.b64 p, [%0], 0; @p bra D; add.u32 n, n, 1; setp.lt.u32 p, n, 4000000; @p bra W; trap;\n"
                 "D: }" :: "r"(b) : "memory");
}
__device__ __forceinline__ bool mbar_test(uint32_t b) {
    uint32_t d; asm volatile("{ .reg .pred p; mbarrier.test_wait.parity.shared::cta.b64 p, [%1], 0; selp.u32 %0, 1, 0, p; }" : "=r"(d) : "r"(b) : "memory"); return d;
}
__device__ __forceinline__ void tma2d(uint32_t dst, const CUtensorMap* m, int c0, int c1, uint32_t bar) {
    asm volatile("cp.async.bulk.tensor.2d.shared::cluster.global.mbarrier::complete_tx::bytes [%0], [%1, {%3, %4}], [%2];"
                 :: "r"(dst), "l"(m), "r"(bar), "r"(c0), "r"(c1) : "memory");
}
__device__ __forceinline__ void tma4d(uint32_t dst, const CUtensorMap* m, int c0, int c1, int c2, int c3, uint32_t bar) {
    asm volatile("cp.async.bulk.tensor.4d.shared::cluster.global.mbarrier::complete_tx::bytes [%0], [%1, {%3, %4, %5, %6}], [%2];"
                 :: "r"(dst), "l"(m), "r"(bar), "r"(c0), "r"(c1), "r"(c2), "r"(c3) : "memory");
}
__device__ __forceinline__ uint32_t mapa(uint32_t a, uint32_t rank) { uint32_t r; asm("mapa.shared::cluster.u32 %0, %1, %2;" : "=r"(r) : "r"(a), "r"(rank)); return r; }
__device__ __forceinline__ void prefetch_map(const CUtensorMap* m) { asm volatile("prefetch.tensormap [%0];" :: "l"(m) : "memory"); }
__device__ __forceinline__ void bar_sync(int id, int n) { asm volatile("bar.sync %0, %1;" :: "r"(id), "r"(n) : "memory"); }
__device__ __forceinline__ void bar_arrive(int id, int n) { asm volatile("bar.arrive %0, %1;" :: "r"(id), "r"(n) : "memory"); }
__device__ __forceinline__ void cluster_arrive_relaxed() { asm volatile("barrier.cluster.arrive.relaxed.aligned;" ::: "memory"); }
__device__ __forceinline__ void cluster_wait() { asm volatile("barrier.cluster.wait.acquire.aligned;" ::: "memory"); }
__device__ __forceinline__ uint32_t ld_rlx32(const void* p) { uint32_t v; asm volatile("ld.relaxed.gpu.global.u32 %0, [%1];" : "=r"(v) : "l"(p) : "memory"); return v; }
__device__ __forceinline__ uint4 ld_rlx128(const void* p) {
    uint4 v; asm volatile("ld.relaxed.gpu.global.v4.u32 {%0,%1,%2,%3}, [%4];" : "=r"(v.x), "=r"(v.y), "=r"(v.z), "=r"(v.w) : "l"(p) : "memory"); return v;
}
__device__ __forceinline__ void st_rlx32(void* p, uint32_t v) { asm volatile("st.relaxed.gpu.global.u32 [%0], %1;" :: "l"(p), "r"(v) : "memory"); }
__device__ __forceinline__ void st_rlx128(void* p, uint32_t x, uint32_t y, uint32_t z, uint32_t w) {
    asm volatile("st.relaxed.gpu.global.v4.u32 [%0], {%1,%2,%3,%4};" :: "l"(p), "r"(x), "r"(y), "r"(z), "r"(w) : "memory");
}
__device__ __forceinline__ uint2 ldg64(const void* p) { uint2 v; asm volatile("ld.global.nc.v2.u32 {%0,%1}, [%2];" : "=r"(v.x), "=r"(v.y) : "l"(p)); return v; }
__device__ __forceinline__ uint4 ldg128(const void* p) { uint4 v; asm volatile("ld.global.nc.v4.u32 {%0,%1,%2,%3}, [%4];" : "=r"(v.x), "=r"(v.y), "=r"(v.z), "=r"(v.w) : "l"(p)); return v; }
__device__ __forceinline__ uint32_t ldg16(const void* p) { uint32_t v; asm volatile("ld.global.nc.u16 %0, [%1];" : "=r"(v) : "l"(p)); return v; }
__device__ __forceinline__ uint32_t clk() { uint32_t t; asm volatile("mov.u32 %0, %clock;" : "=r"(t) :: "memory"); return t; }
__device__ __forceinline__ void spin_until(uint32_t t0, uint32_t d) { while (clk() - t0 < d) { } }
__device__ __forceinline__ float sigmoidf_(float x) { return __fdividef(1.0f, 1.0f + __expf(-x)); }
__device__ __forceinline__ int key_row(uint32_t key) { return 2047 - (int)(key & 2047u); }
__device__ __forceinline__ float key_val(uint32_t key) {
    const uint32_t o = key & 0xffff0000u; return __uint_as_float((o & 0x80000000u) ? (o & 0x7fffffffu) : (~o & 0xffff0000u));
}
#define POLL_GUARD(it) if (++(it) > (1 << 20)) __trap()

constexpr int UT_PL = 2240, UT_STRIDE = 4544;
constexpr int KT_P = 0, KT_P4 = 544 * 4, KT_P8 = KT_P4 + 184 * 4, KT_BYTES = KT_P8 + 144 * 4;
constexpr int KG_STAGE = 33 * 256;
constexpr int OUT_HALF = 2368, OUT_STAGE = 2 * OUT_HALF;
constexpr int SC_UTILE = 0;
constexpr int SC_UT = 32768;
constexpr int SC_KT = SC_UT + 8 * UT_STRIDE;
constexpr int SC_STG = SC_KT + 8 * KT_BYTES;
constexpr int SC_G = SC_STG + 8 * KG_STAGE;
constexpr int SC_OUT = SC_G + 8192;
constexpr int SC_BNC = SC_OUT + 8 * OUT_STAGE;
constexpr int SC_RED = SC_BNC + 2048;
constexpr int SC_MASK = SC_RED + 2048;
constexpr int SC_BAR = SC_MASK + 256;
constexpr int SC_END = SC_BAR + 256;
static_assert(SC_STG % 128 == 0 && SC_OUT % 128 == 0 && SC_KT % 16 == 0, "align");
constexpr int PIECE = 20480;
constexpr int SF_R = 9 * PIECE;
constexpr int SF_XS = SF_R + 36864;
constexpr int SF_LIST = SF_XS, SF_WR = SF_XS + 4096, SF_PART = SF_WR + 2304 + 16;
constexpr int SF_H = SF_XS + 9344;
constexpr int SF_BAR = SF_H + 1280;
constexpr int SF_MAX = SF_BAR + 192, SF_CNT = SF_MAX + 64, SF_TK = SF_CNT + 4, SF_SEL = SF_CNT + 16;
constexpr int SF_END = SF_SEL + 32;
constexpr int SM_TIM = SF_END;
constexpr int SMEM_BYTES = SF_END + 128;
static_assert(SMEM_BYTES <= 232448 && SC_END <= SF_END, "smem");

struct cplx { float re, im; };
struct h2c { __half2 re, im; };
__device__ __forceinline__ cplx csq(cplx a) { cplx r; r.re = a.re * a.re - a.im * a.im; r.im = (a.re * a.im) * 2.f; return r; }
__device__ __forceinline__ cplx cexp2(float x, float y) {
    float m; asm("ex2.approx.ftz.f32 %0, %1;" : "=f"(m) : "f"(x));
    cplx o; o.re = m * __cosf(y); o.im = m * __sinf(y); return o;
}
__device__ __forceinline__ h2c hpack(cplx a, cplx b) { h2c r; const uint32_t x = pack_f16(a.re, b.re), y = pack_f16(a.im, b.im); r.re = *(const __half2*)&x; r.im = *(const __half2*)&y; return r; }
__device__ __forceinline__ h2c hmulc(h2c a, h2c m) { h2c r; r.re = __hfma2(a.re, m.re, __hneg2(__hmul2(a.im, m.im))); r.im = __hfma2(a.re, m.im, __hmul2(a.im, m.re)); return r; }
__device__ __forceinline__ h2c hmulj(h2c a, h2c m) { h2c r; r.re = __hfma2(a.re, m.re, __hmul2(a.im, m.im)); r.im = __hfma2(a.im, m.re, __hneg2(__hmul2(a.re, m.im))); return r; }
__device__ __forceinline__ uint32_t hb(__half2 x) { return *(uint32_t*)&x; }
__device__ __forceinline__ h2c mk(uint32_t x, uint32_t y) { h2c r; r.re = *(__half2*)&x; r.im = *(__half2*)&y; return r; }

__device__ __forceinline__ void kgen(const uint2 (&v)[6], uint32_t logdt, uint32_t stage, uint32_t kt) {
    const int lane = threadIdx.x & 31, g = lane >> 2, t = lane & 3;
    if (lane < 27) {
        const int w = lane < 4 ? 4 * lane : lane < 15 ? 528 + 4 * (lane - 4) : 696 + 4 * (lane - 15);
        sts128(kt + 4 * w, 0, 0, 0, 0);
    }
    const uint32_t we = stage + lane * 8, wo = stage + ((lane * 8) ^ 64);
    sts64(we, 0x3c003c00u, 0u);
    const float dt = rbf(__expf(bf_lo(logdt)));
    cplx W[4];
#pragma unroll
    for (int i = 0; i < 4; i++) {
        auto val = [&](int k) { const uint32_t w = (i & 2) ? v[k].y : v[k].x; return (i & 1) ? bf_hi(w) : bf_lo(w); };
        const float br = val(2), bi = val(3), cr = val(4), ci = val(5);
        W[i].re = cr * br - ci * bi; W[i].im = cr * bi + ci * br;
    }
    float k0 = (W[0].re + W[1].re) + (W[2].re + W[3].re);
    const float mx = fmaxf(fmaxf(fmaxf(fabsf(W[0].re), fabsf(W[0].im)), fmaxf(fabsf(W[1].re), fabsf(W[1].im))), fmaxf(fmaxf(fabsf(W[2].re), fabsf(W[2].im)), fmaxf(fabsf(W[3].re), fabsf(W[3].im))));
    const uint32_t ex = max(__reduce_max_sync(0xffffffffu, __float_as_uint(mx)) >> 23, 10u);
    const float sc = __uint_as_float((263u - ex) << 23), fin = dt * __uint_as_float((ex - 9u) << 23);
#pragma unroll
    for (int o = 16; o; o >>= 1) k0 += __shfl_xor_sync(0xffffffffu, k0, o);
    const float dl = dt * 1.4426950408889634f;
    float acc[5][4];
#pragma unroll
    for (int a = 0; a < 5; a++) acc[a][0] = acc[a][1] = acc[a][2] = acc[a][3] = 0.f;
    uint32_t are = v[0].x, aim = v[1].x;
    cplx Wa = W[0], Wb = W[1];
    const uint32_t rd0 = stage + g * 256 + t * 16 + 64 * (g & 1), rd1 = rd0 ^ 64, rdm = stage + 32 * 256 + t * 16;
#pragma unroll 1
    for (int r = 0; r < 2; r++) {
        auto put = [&](int row, h2c x) { sts64(((row & 1) ? wo : we) + row * 256, hb(x.re), hb(x.im)); };
        const float xa = bf_lo(are) * dl, xb = bf_hi(are) * dl, ya = bf_lo(aim) * dt, yb = bf_hi(aim) * dt;
        cplx a = cexp2(xa, ya), b = cexp2(xb, yb), c = cexp2(64.f * xa, 64.f * ya), d = cexp2(64.f * xb, 64.f * yb);
        h2c c1;
        {
            cplx p, q; const float ar = a.re * sc, ai = a.im * sc, br = b.re * sc, bi = b.im * sc;
            p.re = Wa.re * ar - Wa.im * ai; p.im = -(Wa.re * ai) - Wa.im * ar; q.re = Wb.re * br - Wb.im * bi; q.im = -(Wb.re * bi) - Wb.im * br;
            c1 = hpack(p, q);
        }
        const h2c z1 = hpack(a, b); a = csq(a); b = csq(b);
        put(32, hpack(c, d)); c = csq(c); d = csq(d);
        const h2c z2 = hpack(a, b); a = csq(a); b = csq(b);
        const h2c z128 = hpack(c, d); c = csq(c); d = csq(d);
        const h2c z4 = hpack(a, b); a = csq(a); b = csq(b);
        const h2c z256 = hpack(c, d); c = csq(c); d = csq(d);
        const h2c z8 = hpack(a, b); a = csq(a); b = csq(b);
        const h2c z512 = hpack(c, d);
        const h2c z16 = hpack(a, b); a = csq(a); b = csq(b);
        const h2c z32 = hpack(a, b);
        const h2c c2 = hmulj(c1, z1), c3 = hmulj(c1, z2), c4 = hmulj(c2, z2), c6 = hmulj(c2, z4), c8 = hmulj(c4, z4);
        put(8, c1); put(9, c2); put(10, c3); put(11, c4); put(12, hmulj(c1, z4)); put(13, c6); put(14, hmulj(c3, z4)); put(15, c8);
        const h2c e260 = hmulj(c4, z256), e264 = hmulj(c8, z256), e520 = hmulj(c8, z512), e776 = hmulj(e264, z512);
        put(16, hmulj(c2, z256)); put(17, hmulj(c4, z512)); put(18, e260); put(19, e520); put(20, hmulj(c6, z256)); put(21, hmulj(e260, z512)); put(22, e264); put(23, e776);
        const h2c d0 = hmulj(e520, z512), d2 = hmulj(e776, z512), d4 = hmulj(d0, z512), d6 = hmulj(d2, z512);
        put(24, d0); put(25, d4); put(26, hmulj(d0, z128)); put(27, hmulj(d4, z128)); put(28, d2); put(29, d6); put(30, hmulj(d2, z128)); put(31, hmulj(d6, z128));
        const h2c z24 = hmulc(z8, z16);
        put(1, z8); put(2, z16); put(3, z24); put(4, z32); put(5, hmulc(z8, z32)); put(6, hmulc(z16, z32)); put(7, hmulc(z24, z32));
        __syncwarp();
#pragma unroll
        for (int s = 0; s < 4; s++) {
            const uint32_t rd = ((s & 1) ? rd1 : rd0) + 128 * (s >> 1);
            const uint4 A = lds128(rd), M = lds128(rdm + 64 * s), B0 = lds128(rd + 2048), B1 = lds128(rd + 4096), B2 = lds128(rd + 6144);
#pragma unroll
            for (int e = 0; e < 2; e++) {
                const h2c p0 = e ? mk(A.z, A.w) : mk(A.x, A.y), m = e ? mk(M.z, M.w) : mk(M.x, M.y);
                const h2c p1 = hmulc(p0, m), p2 = hmulc(p1, m), p3 = hmulc(p2, m);
                mma_f16(acc[0], hb(p0.re), hb(p1.re), hb(p0.im), hb(p1.im), e ? B0.z : B0.x, e ? B0.w : B0.y);
                mma_f16(acc[2], hb(p0.re), hb(p1.re), hb(p0.im), hb(p1.im), e ? B1.z : B1.x, e ? B1.w : B1.y);
                mma_f16(acc[4], hb(p0.re), hb(p1.re), hb(p0.im), hb(p1.im), e ? B2.z : B2.x, e ? B2.w : B2.y);
                mma_f16(acc[1], hb(p2.re), hb(p3.re), hb(p2.im), hb(p3.im), e ? B0.z : B0.x, e ? B0.w : B0.y);
                mma_f16(acc[3], hb(p2.re), hb(p3.re), hb(p2.im), hb(p3.im), e ? B1.z : B1.x, e ? B1.w : B1.y);
            }
        }
        __syncwarp();
        are = v[0].y; aim = v[1].y; Wa = W[2]; Wb = W[3];
    }
#pragma unroll
    for (int a = 0; a < 5; a++) { acc[a][0] *= fin; acc[a][1] *= fin; acc[a][2] *= fin; acc[a][3] *= fin; }
    float carry = k0 * dt;
    if (lane == 0) sts32(kt + KT_P + 15 * 4, pack_bf16(carry, 0.f));
#pragma unroll
    for (int q = 0; q < 8; q++) {
        const float hi = q < 4 ? acc[q >> 1][2 * (q & 1) + 1] : acc[q >> 1][2 * (q & 1)];
        const float sh = __shfl_sync(0xffffffffu, hi, (lane + 31) & 31);
        const float prev = lane ? sh : carry;
        carry = sh;
        const float lo = q < 4 ? acc[q >> 1][2 * (q & 1)] : ((lane & 1) ? hi : prev);
        sts64(kt + KT_P + (64 * q + 16) * 4 + lane * 8, pack_bf16(lo, prev), pack_bf16(hi, lo));
    }
    if (lane == 0) { const uint32_t w = pack_bf16(carry, carry); sts128(kt + KT_P + 528 * 4, w, w, w & 0xffff0000u, 0u); }
    const uint32_t a4 = kt + KT_P4 + (24 + 2 * g + (t & 1) + 64 * (t >> 1)) * 4, a8 = kt + KT_P8 + (12 + 16 * t + g) * 4;
#pragma unroll
    for (int q = 0; q < 4; q++) {
        const uint32_t x = pack_bf16(acc[2 + (q >> 1)][2 * (q & 1) + 1], 0.f), y = pack_bf16(acc[4][q], 0.f);
        sts16(a4 + 64 * q, x); sts16(a4 + 64 * q + 18, x);
        sts16(a8 + 256 * (q & 1) + 32 * (q >> 1), y); sts16(a8 + 256 * (q & 1) + 32 * (q >> 1) + 10, y);
    }
    __syncwarp();
}

__device__ __forceinline__ uint32_t band(int e, int c, int h) {
    return (((unsigned)(e - c + h) <= 2u * h) ? 0x3f80u : 0u) | (((unsigned)(e + 1 - c + h) <= 2u * h) ? 0x3f800000u : 0u);
}

__device__ __forceinline__ void conv_warp(const Params& p, uint32_t sb, int cb) {
    const int warp = threadIdx.x >> 5, lane = threadIdx.x & 31, g = lane >> 2, t = lane & 3, mi = lane >> 3, r8 = lane & 7;
    const int rank = cb & 1, ch = 8 * cb + warp;
    const uint32_t kt = sb + SC_KT + warp * KT_BYTES, ut = sb + SC_UT + warp * UT_STRIDE + 128;
    const uint32_t bar_ut = sb + SC_BAR + 32, bar_out = sb + SC_BAR + 48, bar_g = sb + SC_BAR + 112;
    uint32_t dsk;
    {
        uint2 v[6];
        const int o = ch * NST + 4 * lane;
        v[0] = ldg64(p.Are + o); v[1] = ldg64(p.Aim + o); v[2] = ldg64(p.Bre + o); v[3] = ldg64(p.Bim + o); v[4] = ldg64(p.Cre + o); v[5] = ldg64(p.Cim + o);
        const uint32_t logdt = ldg16(p.logdt + ch);
        dsk = ldg16(p.Dskip + ch);
        if (lane < 16) sts128(ut - 128 + (lane >> 3) * UT_PL + r8 * 16, 0, 0, 0, 0);
        kgen(v, logdt, sb + SC_STG + warp * KG_STAGE, kt);
    }
    if (warp == 0) TSTAMP(1);
    cluster_wait();
    float acc[16][4];
    const int d0 = g - 2 * t;
    {
        uint32_t kb[8][2];
#pragma unroll
        for (int l = 0; l < 8; l++) { const uint2 x = lds64(kt + KT_P8 + (6 + 8 * l + d0) * 8); kb[l][0] = x.x; kb[l][1] = x.y; }
        const uint32_t w0 = band(4 * t, 4 + g, 4), w1 = band(4 * t, 4 + g, 3), w2 = band(4 * t + 2, 4 + g, 4), w3 = band(4 * t + 2, 4 + g, 3);
        const uint32_t a0 = ut + g * 16 + (t == 0 ? UT_PL - 8 : t == 3 ? UT_PL : 8 * (t - 1));
        const uint32_t a1 = ut + g * 16 + (t == 0 ? -8 : t == 3 ? 0 : UT_PL - 16 + 8 * (t - 1));
        mbar_wait_cluster(bar_ut);
        if (warp == 0) TSTAMP(2);
#pragma unroll
        for (int j = 0; j < 8; j++) {
            const uint2 x = lds64(a0 + 128 * j - 16), y = lds64(a1 + 128 * j), z = lds64(a0 + 128 * j);
            float X[4], Y[4], Z[4];
            mma_bf0(X, w0, w1, w2, w3, x.x, x.y); mma_bf0(Y, w0, w1, w2, w3, y.x, y.y); mma_bf0(Z, w0, w1, w2, w3, z.x, z.y);
            const uint32_t q0 = pack_bf16(Y[2], Y[3]), q1 = pack_bf16(Z[2], Z[3]), q2 = pack_bf16(X[0], X[1]), q3 = pack_bf16(Y[0], Y[1]);
#pragma unroll
            for (int l = 0; l < 8 - j; l++) {
                if (j == 0) mma_bf0(acc[8 + l], q0, q1, q2, q3, kb[l][0], kb[l][1]);
                else mma_bf(acc[8 + j + l], q0, q1, q2, q3, kb[l][0], kb[l][1]);
            }
        }
    }
    if (warp == 0) TSTAMP(3);
    const uint32_t ub = ut + (mi & 1) * UT_PL + (mi >> 1) * 128 + r8 * 16;
    const uint32_t kp = kt + KT_P + (15 + d0) * 4;
    mbar_wait_cluster(bar_ut + 8);
    {
        const uint32_t c0 = lds32(kp + 512 * 4), c1 = lds32(kp + 520 * 4), c2 = lds32(kp + 504 * 4);
        const uint32_t kv = __byte_perm(lds32(kt + KT_P4 + 151 * 4), 0, 0x1010);
        const uint32_t e0 = kv & ((((unsigned)(d0 - 3) < 2u) ? 0xffffu : 0u) | (((unsigned)(d0 - 4) < 2u) ? 0xffff0000u : 0u));
        const uint32_t e1 = kv & ((((unsigned)(d0 + 5) < 2u) ? 0xffffu : 0u) | (((unsigned)(d0 + 4) < 2u) ? 0xffff0000u : 0u));
        const uint32_t uf = ut + UT_PL - 16 + mi * 128 + r8 * 16;
#pragma unroll
        for (int i = 0; i < 4; i++) acc[i][0] = acc[i][1] = acc[i][2] = acc[i][3] = 0.f;
#pragma unroll
        for (int m4 = 0; m4 < 3; m4++) {
            uint32_t b[2][4], f[4];
            ldsm4(b[0], ub + 512 * m4); ldsm4(b[1], ub + 512 * m4 + 256); ldsm4(f, uf + 512 * m4);
#pragma unroll
            for (int k = 0; k < 4; k++) {
                if (m4 == 0) mma_bf0(acc[4 + k], c0, c1, c2, c0, b[k >> 1][2 * (k & 1)], b[k >> 1][2 * (k & 1) + 1]);
                else mma_bf(acc[4 * m4 + 4 + k], c0, c1, c2, c0, b[k >> 1][2 * (k & 1)], b[k >> 1][2 * (k & 1) + 1]);
            }
            if (m4 < 2) {
#pragma unroll
                for (int k = 0; k < 4; k++) mma_bf(acc[4 * m4 + 8 + k], e0, e1, 0u, e0, b[k >> 1][2 * (k & 1)], b[k >> 1][2 * (k & 1) + 1]);
            }
#pragma unroll
            for (int k = 0; k < 4; k++) mma_bf8(acc[4 * m4 + 4 + k], c1, 0u, f[k]);
            if (m4 < 2) {
#pragma unroll
                for (int k = 0; k < 4; k++) mma_bf8(acc[4 * m4 + 8 + k], e1, 0u, f[k]);
            }
        }
    }
#pragma unroll 1
    for (int j0 = 0; j0 < 8; j0++) {
        uint32_t a[4][4];
        const uint32_t k1 = kp + 64 * j0, u1 = ub - 16 * j0;
#pragma unroll
        for (int j1 = 0; j1 < 4; j1++) { a[j1][0] = lds32(k1 + 512 * j1); a[j1][1] = lds32(k1 + 512 * j1 + 32); a[j1][2] = lds32(k1 + 512 * j1 - 32); a[j1][3] = a[j1][0]; }
#pragma unroll
        for (int m2 = 0; m2 < 8; m2++) {
            uint32_t b[4];
            ldsm4(b, u1 + 256 * m2);
#pragma unroll
            for (int e = 0; e < 2; e++)
#pragma unroll
                for (int j1 = 0; j1 < 4; j1++)
                    if (2 * m2 + e + j1 < 16) mma_bf(acc[2 * m2 + e + j1], a[j1][0], a[j1][1], a[j1][2], a[j1][3], b[2 * e], b[2 * e + 1]);
        }
    }
    if (warp == 0) TSTAMP(4);
    uint32_t kb[5][4];
#pragma unroll
    for (int l = 0; l < 5; l++) { const uint4 x = lds128(kt + KT_P4 + (6 + 8 * l + d0) * 16); kb[l][0] = x.x; kb[l][1] = x.y; kb[l][2] = x.z; kb[l][3] = x.w; }
    const uint32_t w0 = band(2 * t, 2 + g, 2), w1 = band(2 * t, 6 + g, 1), w2 = band(2 * t + 8, 2 + g, 2), w3 = band(2 * t + 8, 6 + g, 1);
    const uint32_t a0 = ut + g * 16 + (t == 0 ? UT_PL - 4 : 4 * (t - 1)), a1 = ut + g * 16 + (t == 0 ? 12 : UT_PL + 4 * (t - 1));
    const uint32_t D2 = __byte_perm(dsk, 0, 0x1010);
    const uint32_t gb = sb + SC_G + (mi & 1) * 2048 + (mi >> 1) * 128 + r8 * 16;
    const bool mine = (mi >> 1) == rank;
    const uint32_t orow = sb + SC_OUT + rank * OUT_HALF + warp * 288, bnc = sb + SC_BNC + warp * 256;
    const uint32_t ow = (mine ? orow : bnc) + (mi & 1) * 128 + r8 * 16, ostep = mine ? OUT_STAGE : 0;
    const uint32_t rem = mapa(orow + lane * 8, rank ^ 1), rbar = mapa(bar_out, rank ^ 1);
    const uint32_t ord = sb + SC_OUT + ((r8 >> 1) & 1) * OUT_HALF + (2 * mi + (r8 & 1)) * 288 + (2 * warp + (r8 >> 2)) * 16;
    const int pos = 2 * warp + (t >> 1), roff = 128 * rank + 16 * (pos & 7) + 8 * (pos >> 3) + g;
    __nv_bfloat16* op = p.out + roff * DM + 16 * (cb >> 1) + 8 * (t & 1);
    mbar_wait(bar_g);
    const uint32_t skip = lds8(sb + SC_MASK + roff);
    auto emit = [&](int q) {
        uint32_t u4[4], g4[4], o4[4], r[4];
        ldsm4t(u4, ub + 256 * q); ldsm4t(g4, gb + 256 * q); ldsm4t(o4, gb + 4096 + 256 * q);
#pragma unroll
        for (int k = 0; k < 4; k++) {
            const uint32_t y = pack_bf16(acc[2 * q + (k >> 1)][2 * (k & 1)], acc[2 * q + (k >> 1)][2 * (k & 1) + 1]);
            r[k] = hadd2(hmul2(g4[k], hadd2(y, hmul2(u4[k], D2))), hmul2(o4[k], u4[k]));
        }
        stsm4t(ow + q * ostep, r[0], r[1], r[2], r[3]);
        __syncwarp();
        const uint2 x = lds64(bnc + lane * 8);
        if (lane == 0) mbar_arrive(bar_out + 8 * q);
        st_async64(rem + q * OUT_STAGE, x.x, x.y, rbar + 8 * q);
        __syncwarp();
    };
    auto store = [&](int q) {
        uint32_t r[4];
        mbar_wait_cluster(bar_out + 8 * q);
        ldsm4t(r, ord + q * OUT_STAGE);
        if (!((skip >> q) & 1)) *(uint4*)(op + q * 256 * DM) = make_uint4(r[0], r[1], r[2], r[3]);
    };
    emit(0); emit(1);
#pragma unroll
    for (int j = 0; j < 12; j++) {
        const uint32_t x0 = lds32(a0 + 128 * j - 16), x1 = lds32(a1 + 128 * j - 16), x2 = lds32(a0 + 128 * j), x3 = lds32(a1 + 128 * j);
        float X[4], Y[4], Z[4];
        mma_bf0(X, w0, w1, w2, w3, x0, x1); mma_bf0(Y, w0, w1, w2, w3, x1, x2); mma_bf0(Z, w0, w1, w2, w3, x2, x3);
        const uint32_t x5 = pack_bf16(X[0], X[1]), xw3 = pack_bf16(X[2], X[3]), y5 = pack_bf16(Y[0], Y[1]), y3 = pack_bf16(Y[2], Y[3]), z5 = pack_bf16(Z[0], Z[1]), z3 = pack_bf16(Z[2], Z[3]);
#pragma unroll
        for (int l = 0; l < 5; l++) if (j + 4 + l < 16) mma_bf(acc[j + 4 + l], y3, z3, y5, z5, kb[l][0], kb[l][1]);
#pragma unroll
        for (int l = 0; l < 5; l++) if (j + 4 + l < 16) mma_bf(acc[j + 4 + l], xw3, y3, x5, y5, kb[l][2], kb[l][3]);
        if (j & 1) { emit(2 + (j >> 1)); store(j >> 1); }
    }
    if (warp == 0) TSTAMP(5);
    store(6); store(7);
    if (warp == 0) TSTAMP(6);
}

__device__ __forceinline__ void conv_helper(const Params& p, const CUtensorMap* mU, uint32_t sb, int cb, uint32_t t0) {
    const int hw = (threadIdx.x >> 5) - 8, lane = threadIdx.x & 31, g = lane >> 2, t = lane & 3, mi = lane >> 3, r8 = lane & 7, ht = threadIdx.x - 256;
    const int rank = cb & 1, slab = cb >> 1;
    const uint32_t bar_box = sb + SC_BAR + 8 * hw, bar_ut = sb + SC_BAR + 32, bar_out = sb + SC_BAR + 48, bar_g = sb + SC_BAR + 112, s_tk = sb + SC_BAR + 120;
    if (lane == 0) {
        mbar_init(bar_box, 1);
        mbar_fence_init();
        mbar_expect(bar_box, 8192);
        if (UDELAY) spin_until(t0, UDELAY);
        tma4d(sb + SC_UTILE + hw * 8192, mU, 16 * slab, 0, 32 * hw + 16 * rank, 0, bar_box);
        mbar_init(bar_out + 16 * hw, 9); mbar_init(bar_out + 16 * hw + 8, 9);
        if (hw < 2) mbar_init(bar_ut + 8 * hw, 3); else if (hw == 2) mbar_init(bar_g, 4);
        mbar_fence_init();
        mbar_expect(bar_out + 16 * hw, 2048); mbar_expect(bar_out + 16 * hw + 8, 2048);
        if (hw < 2) mbar_expect(bar_ut + 8 * hw, 8192);
    }
    __syncwarp();
    cluster_arrive_relaxed();
    if (ht == 96) sts32(s_tk, atomicAdd(&p.scr->launch, 1u));
    if (ht < 64) sts32(sb + SC_MASK + ht * 4, 0);
    cluster_wait();
    {
        const uint32_t src = sb + SC_UTILE + hw * 8192 + (32 * mi + r8) * 32;
        const uint32_t so = (rank ^ (r8 >> 2)) << 4;
        const uint32_t dst = sb + SC_UT + g * UT_STRIDE + 128 + (32 * hw + 16 * rank + t) * 16;
        const uint32_t rdst = mapa(dst, rank ^ 1), rbar = mapa(bar_ut + 8 * (hw >> 1), rank ^ 1);
        mbar_wait(bar_box);
        if (hw == 0) TSTAMP(8); if (hw == 3) TSTAMP(9);
#pragma unroll
        for (int h = 0; h < 2; h++) {
            uint32_t a[4][4], b[4][4];
#pragma unroll
            for (int k = 0; k < 4; k++) { ldsm4t(a[k], src + (so ^ 16) + h * 4096 + k * 256); ldsm4t(b[k], src + so + h * 4096 + k * 256); }
#pragma unroll
            for (int k = 0; k < 4; k++) {
                st_async128(rdst + h * UT_PL + k * 64, a[k][0], a[k][1], a[k][2], a[k][3], rbar);
                sts128(dst + h * UT_PL + k * 64, b[k][0], b[k][1], b[k][2], b[k][3]);
            }
        }
        __syncwarp();
        if (lane == 0) mbar_arrive(bar_ut + 8 * (hw >> 1));
    }
    bar_sync(1, 128);
    const unsigned ep = lds32(s_tk) / NCTA + 1;
    uint32_t key;
    for (int it = 0;;) {
        key = ld_rlx32(&p.scr->sel[ht >> 4]);
        if (__all_sync(0xffffffffu, ((key >> 11) & 31u) == (ep & 31u))) break;
        POLL_GUARD(it);
        __nanosleep(200);
    }
    if (hw == 0) TSTAMP(10);
    const int row = key_row(key), c = ht & 15;
    const uint32_t xv = ldg16(p.u + row * DM + 16 * slab + c);
#pragma unroll 1
    for (int k = 0; k < 2; k++) {
        const int chunk = ht + 128 * k;
        uint4 a, b;
        const uint32_t tg = (ep & 3u) * 0x4000u;
        for (int it = 0;;) {
            a = ld_rlx128(&p.scr->rec[8 * chunk]); b = ld_rlx128(&p.scr->rec[8 * chunk + 4]);
            if ((((a.x ^ tg) | (a.y ^ tg) | (a.z ^ tg) | (a.w ^ tg) | (b.x ^ tg) | (b.y ^ tg) | (b.z ^ tg) | (b.w ^ tg)) & 0xc000u) == 0) break;
            POLL_GUARD(it);
        }
        const uint32_t g0 = __byte_perm(a.x, a.y, 0x5410) & 0x3fff3fffu, g1 = __byte_perm(a.z, a.w, 0x5410) & 0x3fff3fffu;
        const uint32_t g2 = __byte_perm(b.x, b.y, 0x5410) & 0x3fff3fffu, g3 = __byte_perm(b.z, b.w, 0x5410) & 0x3fff3fffu;
        const uint32_t d = sb + SC_G + (chunk & 1) * 2048 + (chunk >> 1) * 16;
        sts128(d, g0, g1, g2, g3);
        sts128(d + 4096, hsub2(0x3f803f80u, g0), hsub2(0x3f803f80u, g1), hsub2(0x3f803f80u, g2), hsub2(0x3f803f80u, g3));
    }
    bar_sync(1, 128);
    const uint32_t oma = sb + SC_G + 4096 + ((row >> 3) & 1) * 2048 + (row >> 4) * 16 + (row & 7) * 2;
    const float om = bf_lo(lds16(oma));
    __syncwarp();
    if (c == 0) {
        sts16(oma, 0);
        asm volatile("red.shared.or.b32 [%0], %1;" :: "r"(sb + SC_MASK + (row & 252)), "r"(1u << (8 * (row & 3) + (row >> 8))) : "memory");
    }
    __syncwarp();
    if (lane == 0) mbar_arrive(bar_g);
    if (hw == 0) TSTAMP(11);
    const float rs = rbf(sigmoidf_(key_val(key)));
    const uint4* src = p.scr->part + (slab * NFFN + 15 * hw) * 32;
    for (int it = 0;;) {
        const uint32_t w = ld_rlx32(src + min(lane, 14) * 32 + 31);
        if (__all_sync(0xffffffffu, (w & 3u) == (ep & 3u))) break;
        POLL_GUARD(it);
        __nanosleep(20);
    }
    if (hw == 0) TSTAMP(12);
    float s0, s1, s2, s3;
    for (int it = 0;;) {
        uint4 v[15];
#pragma unroll
        for (int k = 0; k < 15; k++) v[k] = ld_rlx128(src + k * 32 + lane);
        uint32_t bad = 0; s0 = s1 = s2 = s3 = 0.f;
#pragma unroll
        for (int k = 0; k < 15; k++) {
            bad |= (v[k].x ^ ep) | (v[k].y ^ ep); bad |= (v[k].z ^ ep) | (v[k].w ^ ep);
            s0 += __uint_as_float(v[k].x); s1 += __uint_as_float(v[k].y); s2 += __uint_as_float(v[k].z); s3 += __uint_as_float(v[k].w);
        }
        if ((bad & 3u) == 0) break;
        POLL_GUARD(it);
    }
    sts128(sb + SC_RED + ht * 16, __float_as_uint(s0), __float_as_uint(s1), __float_as_uint(s2), __float_as_uint(s3));
    bar_sync(1, 128);
    if (hw == 0) TSTAMP(13);
    if (((row >> 7) & 1) == rank) {
        const int tok = ht >> 4;
        const uint32_t ra = sb + SC_RED + ((c & 7) * 4 + (tok >> 1)) * 16 + ((c >> 3) * 2 + (tok & 1)) * 4;
        const float y = rbf((__uint_as_float(lds32(ra)) + __uint_as_float(lds32(ra + 512))) + (__uint_as_float(lds32(ra + 1024)) + __uint_as_float(lds32(ra + 1536))));
        const float b = rbf(bf_lo(xv) + rbf(y * rs));
        mbar_wait_cluster(bar_out + 8 * (row >> 8));
        const float ga = bf_lo(lds16(sb + SC_OUT + (row >> 8) * OUT_STAGE + (c >> 3) * OUT_HALF + (c & 7) * 288 + (((row >> 4) & 7) + (row & 8)) * 16 + (row & 7) * 2));
        *(unsigned short*)(p.out + row * DM + 16 * slab + c) = (unsigned short)pack_bf16(ga + rbf(om * b), 0.f);
    }
    if (hw == 0) TSTAMP(14);
}

__device__ __forceinline__ void ffn_cta(const Params& p, const CUtensorMap* mR, const CUtensorMap* mG64, const CUtensorMap* mU64, const CUtensorMap* mG16,
                                        const CUtensorMap* mU16, const CUtensorMap* mWd, uint32_t sb, int f, uint32_t t0) {
    const int tid = threadIdx.x, warp = tid >> 5, lane = tid & 31, g = lane >> 2, t = lane & 3, mi = lane >> 3, r8 = lane & 7;
    const bool wide = f < 48;
    const int nunit = wide ? 10 : 8;
    const uint32_t bar_w = sb + SF_BAR, bar_d = bar_w + 72, bar_r = bar_w + 112, bar_sel = bar_w + 152, bar_free = bar_w + 160;
    unsigned ep;
    if (warp == 11) {
        if (lane == 0) {
            prefetch_map(mG64); prefetch_map(mU64); prefetch_map(mG16); prefetch_map(mU16); prefetch_map(mWd);
#pragma unroll 1
            for (int i = 0; i < 14; i++) mbar_init(bar_w + 8 * i, 1);
            mbar_init(bar_sel, 8); mbar_init(bar_free, nunit); mbar_init(bar_free + 8, nunit); mbar_init(bar_free + 16, nunit);
            mbar_fence_init();
        }
        __syncwarp();
        bar_arrive(1, NTHR);
        if (lane == 0) {
            spin_until(t0, WDELAY);
#pragma unroll 1
            for (int n = 0; n < 9; n++) {
                if (n >= WWIN) { int it = 0; while (!mbar_test(bar_w + 8 * (n - WWIN)) && !mbar_test(bar_free)) POLL_GUARD(it); }
                if (n == 8) mbar_wait(bar_sel);
                const uint32_t b = bar_w + 8 * n, d = sb + n * PIECE;
                mbar_expect(b, wide ? PIECE : 16384);
                tma2d(d, mG64, 64 * f, 64 * n, b); tma2d(d + 8192, mU64, 64 * f, 64 * n, b);
                if (wide) { tma2d(d + 16384, mG16, 3840 + 16 * f, 64 * n, b); tma2d(d + 18432, mU16, 3840 + 16 * f, 64 * n, b); }
            }
            TSTAMP(10);
#pragma unroll 1
            for (int i = 0; i < nunit / 2; i++) {
                if (i < 2) { int it = 0; while (!mbar_test(bar_w + 8 * (9 + i - WWIN)) && !mbar_test(bar_free)) POLL_GUARD(it); }
                else mbar_wait(bar_free + 8 * (i - 2));
                mbar_expect(bar_d + 8 * i, 18432);
                tma2d(i < 2 ? sb + SF_R + i * 18432 : sb + (i - 2) * PIECE, mWd, 0, 9 * (i < 4 ? 64 * f + 16 * i : 3840 + 16 * f), bar_d + 8 * i);
            }
            TSTAMP(11);
        }
        __syncwarp();
    } else {
        const int ng = f >= 44 ? 5 : 4, r0 = f >= 44 ? 1408 + 40 * (f - 44) : 32 * f;
        const int grp = warp >> 1, kh = warp & 1;
        const uint32_t rows = grp < 4 ? sb + SF_R + grp * 9216 : sb + 8 * PIECE;
        if (lane == 0 && kh == 0 && grp < ng) {
            mbar_init(bar_r + 8 * grp, 1);
            mbar_fence_init();
            mbar_expect(bar_r + 8 * grp, 9216);
            spin_until(t0, RDELAY);
            tma2d(rows, mR, 0, 9 * (r0 + 8 * grp), bar_r + 8 * grp);
        }
        if (kh == 1) {
            const int i = 32 * grp + lane;
            if (i < 144) { const uint4 w = ldg128((const uint4*)(i < 72 ? p.wr : p.gatew - DM) + i); sts128(sb + SF_WR + i * 16, w.x, w.y, w.z, w.w); }
        }
        if (warp == 10) {
#pragma unroll 1
            for (int i = lane; i < 256; i += 32) sts128(sb + SF_LIST + i * 16, 0, 0, 0, 0);
            if (lane == 0) sts64(sb + SF_CNT, 0, atomicAdd(&p.scr->launch, 1u));
        }
        bar_sync(1, NTHR);
        ep = lds32(sb + SF_TK) / NCTA + 1;
        if (grp < ng) {
            uint32_t wr[10][2], gw[9][4];
            const uint32_t wa = sb + SF_WR + kh * 576 + (2 * mi + (r8 & 1)) * 16, ga = sb + SF_WR + 1152 + kh * 576 + mi * 16;
#pragma unroll
            for (int i = 0; i < 5; i++) { uint32_t x[4]; ldsm4(x, wa + 128 * i); wr[2 * i][0] = x[0]; wr[2 * i][1] = x[1]; wr[2 * i + 1][0] = x[2]; wr[2 * i + 1][1] = x[3]; }
#pragma unroll
            for (int i = 0; i < 9; i++) ldsm4(gw[i], ga + 64 * i);
            float cr[4] = {0.f, 0.f, 0.f, 0.f}, cg[4] = {0.f, 0.f, 0.f, 0.f};
            mbar_wait(bar_r + 8 * grp);
            if (warp == 0) TSTAMP(1);
#pragma unroll
            for (int i = 0; i < 9; i++) {
                const int c = 36 * kh + 4 * i + mi, line = 9 * r8 + (c >> 3);
                uint32_t a[4];
                ldsm4(a, rows + line * 128 + (((c ^ line) & 7) << 4));
                mma_bf(cr, a[0], a[1], a[2], a[3], wr[i][0], wr[i][1]);
                mma_bf(cg, hmul2(a[0], gw[i][0]), hmul2(a[1], gw[i][1]), hmul2(a[2], gw[i][2]), hmul2(a[3], gw[i][3]), 0x3f803f80u, 0x3f803f80u);
            }
            const float sr = cr[0] + cr[3], sg = cg[0] + cg[2];
            if (kh == 1) {
                if (t == 0) sts64(sb + SF_PART + (grp * 8 + g) * 8, __float_as_uint(sr), __float_as_uint(sg));
                bar_arrive(2 + grp, 64);
            } else {
                bar_sync(2 + grp, 64);
                if (t == 0) {
                    const uint2 o = lds64(sb + SF_PART + (grp * 8 + g) * 8);
                    const uint32_t gg = pack_bf16(sigmoidf_(rbf(sg + __uint_as_float(o.y))), 0.f);
                    uint32_t rb = pack_bf16(0.f, sr + __uint_as_float(o.x));
                    rb = (rb & 0x80000000u) ? ~rb : (rb | 0x80000000u);
                    st_rlx32(&p.scr->rec[r0 + 8 * grp + g], (rb & 0xffff0000u) | ((ep & 3u) << 14) | (gg & 0x3fffu));
                }
                if (warp == 0) TSTAMP(2);
            }
        }
        if (warp < 8) {
            uint32_t k[8];
            const uint32_t tg = (ep & 3u) * 0x4000u;
            for (int it = 0;;) {
                const uint4 a = ld_rlx128(&p.scr->rec[4 * tid]), b = ld_rlx128(&p.scr->rec[1024 + 4 * tid]);
                k[0] = a.x; k[1] = a.y; k[2] = a.z; k[3] = a.w; k[4] = b.x; k[5] = b.y; k[6] = b.z; k[7] = b.w;
                if (__all_sync(0xffffffffu, (((a.x ^ tg) | (a.y ^ tg) | (a.z ^ tg) | (a.w ^ tg) | (b.x ^ tg) | (b.y ^ tg) | (b.z ^ tg) | (b.w ^ tg)) & 0xc000u) == 0)) break;
                POLL_GUARD(it);
            }
            if (warp == 0) TSTAMP(3);
#pragma unroll
            for (int i = 0; i < 8; i++) k[i] = (k[i] & 0xffff0000u) | (uint32_t)(2047 - 1024 * (i >> 2) - (i & 3) - 4 * tid);
            const uint32_t m0 = __reduce_max_sync(0xffffffffu, max(max(k[0], k[1]), max(k[2], k[3]))), m1 = __reduce_max_sync(0xffffffffu, max(max(k[4], k[5]), max(k[6], k[7])));
            if (lane == 0) sts64(sb + SF_MAX + warp * 8, m0, m1);
            bar_sync(7, 256);
            uint32_t thr;
            {
                const uint32_t m = lds32(sb + SF_MAX + (lane & 15) * 4);
                int rk = 0;
#pragma unroll
                for (int i = 0; i < 4; i++) { const uint4 x = lds128(sb + SF_MAX + 16 * i); rk += (x.x > m) + (x.y > m) + (x.z > m) + (x.w > m); }
                thr = __reduce_max_sync(0xffffffffu, rk == 7 ? m : 0u);
            }
#pragma unroll
            for (int i = 0; i < 8; i++)
                if (k[i] >= thr) { uint32_t s; asm volatile("atom.shared.add.u32 %0, [%1], 1;" : "=r"(s) : "r"(sb + SF_CNT) : "memory"); sts32(sb + SF_LIST + 4 * s, k[i]); }
            bar_sync(7, 256);
            const int n = lds32(sb + SF_CNT);
            uint32_t key = 0;
#pragma unroll 1
            for (int base = 0; base < n; base += 32) {
                const uint32_t m = lds32(sb + SF_LIST + (base + lane) * 4);
                int rk = 0;
#pragma unroll 1
                for (int i = 0; i < n; i += 8) {
                    const uint4 x = lds128(sb + SF_LIST + 4 * i), y = lds128(sb + SF_LIST + 4 * i + 16);
                    rk += (x.x > m) + (x.y > m) + (x.z > m) + (x.w > m) + (y.x > m) + (y.y > m) + (y.z > m) + (y.w > m);
                }
                if (rk == warp && base + lane < n) key = m;
            }
            key = __reduce_max_sync(0xffffffffu, key);
            if (warp == 0) TSTAMP(4);
            const uint4* xr = (const uint4*)(p.u + key_row(key) * DM);
            const uint4 x0 = ldg128(xr + lane), x1 = ldg128(xr + 32 + lane), x2 = ldg128(xr + 64 + r8);
            if (lane == 0) { sts32(sb + SF_SEL + warp * 4, key | ((ep & 31u) << 11)); mbar_arrive(bar_sel); }
            bar_sync(7, 256);
            if (f == 0 && tid < 8) st_rlx32(&p.scr->sel[tid], lds32(sb + SF_SEL + tid * 4));
            const uint32_t xd = sb + SF_XS + warp * 1168 + lane * 16;
            sts128(xd, x0.x, x0.y, x0.z, x0.w); sts128(xd + 512, x1.x, x1.y, x1.z, x1.w);
            if (lane < 8) sts128(xd + 1024, x2.x, x2.y, x2.z, x2.w);
        }
        if (warp < nunit) {
            bar_sync(8, 32 * nunit);
            if (warp == 0) TSTAMP(5);
            const int kr = 8 * (mi >> 1) + r8;
            uint32_t wa = warp < 8 ? sb + (mi & 1) * 8192 + kr * 128 + ((warp ^ r8) << 4) : sb + 16384 + (mi & 1) * 2048 + kr * 32 + (((warp ^ (r8 >> 2)) & 1) << 4);
            const uint32_t ws = warp < 8 ? 2048 : 512;
            uint32_t xa = sb + SF_XS + r8 * 1168 + mi * 16;
            float c0[4] = {0.f, 0.f, 0.f, 0.f}, c1[4] = {0.f, 0.f, 0.f, 0.f};
#pragma unroll 1
            for (int n = 0; n < 9; n++) {
                uint32_t x[2][4], a[4][4];
                ldsm4(x[0], xa); ldsm4(x[1], xa + 64);
                mbar_wait(bar_w + 8 * n);
#pragma unroll
                for (int s = 0; s < 4; s++) ldsm4t(a[s], wa + s * ws);
                mma_bf(c0, a[0][0], a[0][1], a[0][2], a[0][3], x[0][0], x[0][1]);
                mma_bf(c1, a[1][0], a[1][1], a[1][2], a[1][3], x[0][2], x[0][3]);
                mma_bf(c0, a[2][0], a[2][1], a[2][2], a[2][3], x[1][0], x[1][1]);
                mma_bf(c1, a[3][0], a[3][1], a[3][2], a[3][3], x[1][2], x[1][3]);
                if (n < 3) {
                    asm volatile("" :: "r"(a[0][0]), "r"(a[1][0]), "r"(a[2][0]), "r"(a[3][0]) : "memory");
                    __syncwarp();
                    if (lane == 0) mbar_arrive(bar_free + 8 * n);
                }
                wa += PIECE; xa += 128;
            }
            if (warp == 0) TSTAMP(6);
            float h[2];
#pragma unroll
            for (int e = 0; e < 2; e++) {
                const float gv = rbf(c0[e] + c1[e]), uv = rbf(c0[2 + e] + c1[2 + e]);
                h[e] = rbf(gv * sigmoidf_(gv)) * uv;
            }
            uint32_t hp = pack_bf16(h[0], h[1]);
            asm volatile("movmatrix.sync.aligned.m8n8.trans.b16 %0, %0;" : "+r"(hp));
            sts32(sb + SF_H + (warp >> 1) * 256 + lane * 8 + (warp & 1) * 4, hp);
        }
    }
    bar_sync(9, NTHR);
    ep = lds32(sb + SF_TK) / NCTA + 1;
    float d[3][4];
    uint32_t off[3];
#pragma unroll
    for (int j = 0; j < 3; j++) {
        const int tile = 3 * warp + j, line = 9 * (8 * (mi >> 1) + r8) + (tile >> 2);
        off[j] = line * 128 + ((((2 * tile + (mi & 1)) ^ line) & 7) << 4);
        d[j][0] = d[j][1] = d[j][2] = d[j][3] = 0.f;
    }
#pragma unroll 1
    for (int i = 0; i < nunit / 2; i++) {
        const uint2 hv = lds64(sb + SF_H + i * 256 + lane * 8);
        const uint32_t base = i < 2 ? sb + SF_R + i * 18432 : sb + (i - 2) * PIECE;
        mbar_wait(bar_d + 8 * i);
        uint32_t a[3][4];
#pragma unroll
        for (int j = 0; j < 3; j++) ldsm4t(a[j], base + off[j]);
#pragma unroll
        for (int j = 0; j < 3; j++) mma_bf(d[j], a[j][0], a[j][1], a[j][2], a[j][3], hv.x, hv.y);
    }
    if (warp == 0) TSTAMP(7);
#pragma unroll
    for (int j = 0; j < 3; j++) {
        auto tagd = [&](float x) { return (__float_as_uint(x) & ~3u) | (ep & 3u); };
        st_rlx128(p.scr->part + ((3 * warp + j) * NFFN + f) * 32 + lane, tagd(d[j][0]), tagd(d[j][1]), tagd(d[j][2]), tagd(d[j][3]));
    }
    if (warp == 0) TSTAMP(8);
}

__global__ void __cluster_dims__(2, 1, 1) __launch_bounds__(NTHR, 1)
fused_kernel(const Params p, const __grid_constant__ CUtensorMap mU, const __grid_constant__ CUtensorMap mR, const __grid_constant__ CUtensorMap mG64,
             const __grid_constant__ CUtensorMap mU64, const __grid_constant__ CUtensorMap mG16, const __grid_constant__ CUtensorMap mU16,
             const __grid_constant__ CUtensorMap mWd) {
    extern __shared__ __align__(1024) uint8_t smem_raw[];
    const uint32_t sb = smem_u32(smem_raw);
    const uint32_t t0 = clk();
    const int bx = blockIdx.x;
    if (bx >= FFN0 && bx < FFN0 + NFFN) ffn_cta(p, &mR, &mG64, &mU64, &mG16, &mU16, &mWd, sb, bx - FFN0, t0);
    else {
        const int cb = bx < FFN0 ? bx : bx - NFFN;
        if (threadIdx.x < 256) { cluster_arrive_relaxed(); conv_warp(p, sb, cb); }
        else conv_helper(p, &mU, sb, cb, t0);
    }
}

typedef CUresult (*EncodeFn)(CUtensorMap*, CUtensorMapDataType, cuuint32_t, void*, const cuuint64_t*, const cuuint64_t*, const cuuint32_t*, const cuuint32_t*,
                             CUtensorMapInterleave, CUtensorMapSwizzle, CUtensorMapL2promotion, CUtensorMapFloatOOBfill);

CUtensorMap make_map(EncodeFn fn, const void* base, uint64_t inner, uint64_t outer, uint32_t bi, uint32_t bo, CUtensorMapSwizzle sw,
                     CUtensorMapL2promotion pr = CU_TENSOR_MAP_L2_PROMOTION_NONE) {
    CUtensorMap m;
    cuuint64_t dims[2] = {inner, outer};
    cuuint64_t strides[1] = {inner * 2};
    cuuint32_t box[2] = {bi, bo};
    cuuint32_t es[2] = {1, 1};
    fn(&m, CU_TENSOR_MAP_DATA_TYPE_BFLOAT16, 2, (void*)base, dims, strides, box, es, CU_TENSOR_MAP_INTERLEAVE_NONE, sw, pr, CU_TENSOR_MAP_FLOAT_OOB_FILL_NONE);
    return m;
}

}

extern "C" void kernel_launch(void* const* d_in, const int* in_sizes, int n_in, void* d_out, int out_size) {
    (void)in_sizes; (void)n_in; (void)out_size;
    static EncodeFn fn = nullptr;
    static Scratch* scr = nullptr;
    if (!fn) {
        void* ptr = nullptr; cudaDriverEntryPointQueryResult qr;
        cudaGetDriverEntryPoint("cuTensorMapEncodeTiled", &ptr, cudaEnableDefault, &qr);
        fn = (EncodeFn)ptr;
        cudaGetSymbolAddress((void**)&scr, g_scr);
        cudaFuncSetAttribute(fused_kernel, cudaFuncAttributeMaxDynamicSharedMemorySize, SMEM_BYTES);
    }
    typedef const __nv_bfloat16* bp;
    Params p;
    p.u = (bp)d_in[0]; p.Are = (bp)d_in[1]; p.Aim = (bp)d_in[2]; p.Bre = (bp)d_in[3]; p.Bim = (bp)d_in[4]; p.Cre = (bp)d_in[5]; p.Cim = (bp)d_in[6];
    p.logdt = (bp)d_in[7]; p.Dskip = (bp)d_in[8]; p.wr = (bp)d_in[10]; p.gatew = (bp)d_in[14];
    p.out = (__nv_bfloat16*)d_out; p.scr = scr;
    CUtensorMap mU;
    {
        cuuint64_t dims[4] = {DM, 2, L_SEQ / 16, 8};
        cuuint64_t strides[3] = {DM * 2, 16 * DM * 2, 2 * DM * 2};
        cuuint32_t box[4] = {16, 2, 16, 8};
        cuuint32_t es[4] = {1, 1, 1, 1};
        fn(&mU, CU_TENSOR_MAP_DATA_TYPE_BFLOAT16, 4, d_in[0], dims, strides, box, es, CU_TENSOR_MAP_INTERLEAVE_NONE, CU_TENSOR_MAP_SWIZZLE_32B,
           CU_TENSOR_MAP_L2_PROMOTION_NONE, CU_TENSOR_MAP_FLOAT_OOB_FILL_NONE);
    }
    const CUtensorMap mR = make_map(fn, d_in[0], 64, L_SEQ * 9, 64, 72, CU_TENSOR_MAP_SWIZZLE_128B);
    const CUtensorMap mG64 = make_map(fn, d_in[11], FF, DM, 64, 64, CU_TENSOR_MAP_SWIZZLE_128B);
    const CUtensorMap mU64 = make_map(fn, d_in[12], FF, DM, 64, 64, CU_TENSOR_MAP_SWIZZLE_128B);
    const CUtensorMap mG16 = make_map(fn, d_in[11], FF, DM, 16, 64, CU_TENSOR_MAP_SWIZZLE_32B, CU_TENSOR_MAP_L2_PROMOTION_L2_128B);
    const CUtensorMap mU16 = make_map(fn, d_in[12], FF, DM, 16, 64, CU_TENSOR_MAP_SWIZZLE_32B, CU_TENSOR_MAP_L2_PROMOTION_L2_128B);
    const CUtensorMap mWd = make_map(fn, d_in[13], 64, FF * 9, 64, 144, CU_TENSOR_MAP_SWIZZLE_128B);
    fused_kernel<<<NCTA, NTHR, SMEM_BYTES>>>(p, mU, mR, mG64, mU64, mG16, mU16, mWd);
}
```

```cpp
#include <cuda_runtime.h>
#include <cuda_bf16.h>
#include <cuda_fp16.h>
#include <cuda.h>
#include <stdint.h>

#define RDELAY 1000
#define UDELAY 0
#define WDELAY 1800
#define PDELAY 900
#define WWIN 3

namespace {

constexpr int L_SEQ = 2048, DM = 576, NST = 128, FF = 4608;
constexpr int NCTA = 132, NFFN = 60, FFN0 = 8, NTHR = 384;

struct Scratch {
    unsigned launch; unsigned pad0[31];
    uint32_t sel[32];
    uint32_t rec[L_SEQ];
    uint4 part[36 * NFFN * 32];
};
__device__ Scratch g_scr;

struct Params {
    const __nv_bfloat16 *Are, *Aim, *Bre, *Bim, *Cre, *Cim, *logdt, *Dskip, *u, *wr, *gatew;
    __nv_bfloat16* out;
    Scratch* scr;
};

#define TSTAMP(i)

__device__ __forceinline__ uint32_t smem_u32(const void* p) { return (uint32_t)__cvta_generic_to_shared(p); }
__device__ __forceinline__ uint32_t pack_bf16(float lo, float hi) { uint32_t r; asm("cvt.rn.bf16x2.f32 %0, %1, %2;" : "=r"(r) : "f"(hi), "f"(lo)); return r; }
__device__ __forceinline__ uint32_t pack_f16(float lo, float hi) { uint32_t r; asm("cvt.rn.f16x2.f32 %0, %1, %2;" : "=r"(r) : "f"(hi), "f"(lo)); return r; }
__device__ __forceinline__ float bf_lo(uint32_t w) { return __uint_as_float(w << 16); }
__device__ __forceinline__ float bf_hi(uint32_t w) { return __uint_as_float(w & 0xffff0000u); }
__device__ __forceinline__ float rbf(float x) { return bf_lo(pack_bf16(x, 0.f)); }
__device__ __forceinline__ uint32_t hmul2(uint32_t a, uint32_t b) { __nv_bfloat162 r = __hmul2_rn(*(__nv_bfloat162*)&a, *(__nv_bfloat162*)&b); return *(uint32_t*)&r; }
__device__ __forceinline__ uint32_t hadd2(uint32_t a, uint32_t b) { __nv_bfloat162 r = __hadd2_rn(*(__nv_bfloat162*)&a, *(__nv_bfloat162*)&b); return *(uint32_t*)&r; }
__device__ __forceinline__ uint32_t hsub2(uint32_t a, uint32_t b) { __nv_bfloat162 r = __hsub2_rn(*(__nv_bfloat162*)&a, *(__nv_bfloat162*)&b); return *(uint32_t*)&r; }
__device__ __forceinline__ void mma_bf(float (&c)[4], uint32_t a0, uint32_t a1, uint32_t a2, uint32_t a3, uint32_t b0, uint32_t b1) {
    asm("mma.sync.aligned.m16n8k16.row.col.f32.bf16.bf16.f32 {%0,%1,%2,%3}, {%4,%5,%6,%7}, {%8,%9}, {%0,%1,%2,%3};"
        : "+f"(c[0]), "+f"(c[1]), "+f"(c[2]), "+f"(c[3]) : "r"(a0), "r"(a1), "r"(a2), "r"(a3), "r"(b0), "r"(b1));
}
__device__ __forceinline__ void mma_bf0(float (&c)[4], uint32_t a0, uint32_t a1, uint32_t a2, uint32_t a3, uint32_t b0, uint32_t b1) {
    asm("mma.sync.aligned.m16n8k16.row.col.f32.bf16.bf16.f32 {%0,%1,%2,%3}, {%4,%5,%6,%7}, {%8,%9}, {%10,%10,%10,%10};"
        : "=f"(c[0]), "=f"(c[1]), "=f"(c[2]), "=f"(c[3]) : "r"(a0), "r"(a1), "r"(a2), "r"(a3), "r"(b0), "r"(b1), "f"(0.f));
}
__device__ __forceinline__ void mma_bf8(float (&c)[4], uint32_t a0, uint32_t a1, uint32_t b0) {
    asm("mma.sync.aligned.m16n8k8.row.col.f32.bf16.bf16.f32 {%0,%1,%2,%3}, {%4,%5}, {%6}, {%0,%1,%2,%3};"
        : "+f"(c[0]), "+f"(c[1]), "+f"(c[2]), "+f"(c[3]) : "r"(a0), "r"(a1), "r"(b0));
}
__device__ __forceinline__ void mma_f16(float (&c)[4], uint32_t a0, uint32_t a1, uint32_t a2, uint32_t a3, uint32_t b0, uint32_t b1) {
    asm("mma.sync.aligned.m16n8k16.row.col.f32.f16.f16.f32 {%0,%1,%2,%3}, {%4,%5,%6,%7}, {%8,%9}, {%0,%1,%2,%3};"
        : "+f"(c[0]), "+f"(c[1]), "+f"(c[2]), "+f"(c[3]) : "r"(a0), "r"(a1), "r"(a2), "r"(a3), "r"(b0), "r"(b1));
}
__device__ __forceinline__ uint32_t lds16(uint32_t a) { uint32_t v; asm volatile("ld.shared.u16 %0, [%1];" : "=r"(v) : "r"(a)); return v; }
__device__ __forceinline__ uint32_t lds8(uint32_t a) { uint32_t v; asm volatile("ld.shared.u8 %0, [%1];" : "=r"(v) : "r"(a)); return v; }
__device__ __forceinline__ uint32_t lds32(uint32_t a) { uint32_t v; asm volatile("ld.shared.u32 %0, [%1];" : "=r"(v) : "r"(a)); return v; }
__device__ __forceinline__ uint2 lds64(uint32_t a) { uint2 v; asm volatile("ld.shared.v2.u32 {%0,%1}, [%2];" : "=r"(v.x), "=r"(v.y) : "r"(a)); return v; }
__device__ __forceinline__ uint4 lds128(uint32_t a) { uint4 v; asm volatile("ld.shared.v4.u32 {%0,%1,%2,%3}, [%4];" : "=r"(v.x), "=r"(v.y), "=r"(v.z), "=r"(v.w) : "r"(a)); return v; }
__device__ __forceinline__ void ldsm4(uint32_t (&r)[4], uint32_t a) {
    asm volatile("ldmatrix.sync.aligned.m8n8.x4.shared.b16 {%0,%1,%2,%3}, [%4];" : "=r"(r[0]), "=r"(r[1]), "=r"(r[2]), "=r"(r[3]) : "r"(a));
}
__device__ __forceinline__ void ldsm4t(uint32_t (&r)[4], uint32_t a) {
    asm volatile("ldmatrix.sync.aligned.m8n8.x4.trans.shared.b16 {%0,%1,%2,%3}, [%4];" : "=r"(r[0]), "=r"(r[1]), "=r"(r[2]), "=r"(r[3]) : "r"(a));
}
__device__ __forceinline__ void sts16(uint32_t a, uint32_t v) { asm volatile("st.shared.u16 [%0], %1;" :: "r"(a), "h"((unsigned short)v) : "memory"); }
__device__ __forceinline__ void sts32(uint32_t a, uint32_t v) { asm volatile("st.shared.u32 [%0], %1;" :: "r"(a), "r"(v) : "memory"); }
__device__ __forceinline__ void sts64(uint32_t a, uint32_t x, uint32_t y) { asm volatile("st.shared.v2.u32 [%0], {%1,%2};" :: "r"(a), "r"(x), "r"(y) : "memory"); }
__device__ __forceinline__ void sts128(uint32_t a, uint32_t x, uint32_t y, uint32_t z, uint32_t w) {
    asm volatile("st.shared.v4.u32 [%0], {%1,%2,%3,%4};" :: "r"(a), "r"(x), "r"(y), "r"(z), "r"(w) : "memory");
}
__device__ __forceinline__ void stsm4t(uint32_t a, uint32_t r0, uint32_t r1, uint32_t r2, uint32_t r3) {
    asm volatile("stmatrix.sync.aligned.m8n8.x4.trans.shared.b16 [%0], {%1,%2,%3,%4};" :: "r"(a), "r"(r0), "r"(r1), "r"(r2), "r"(r3) : "memory");
}
__device__ __forceinline__ void st_async64(uint32_t a, uint32_t x, uint32_t y, uint32_t bar) {
    asm volatile("st.async.weak.shared::cluster.mbarrier::complete_tx::bytes.v2.b32 [%0], {%1,%2}, [%3];" :: "r"(a), "r"(x), "r"(y), "r"(bar) : "memory");
}
__device__ __forceinline__ void st_async128(uint32_t a, uint32_t x, uint32_t y, uint32_t z, uint32_t w, uint32_t bar) {
    asm volatile("st.async.weak.shared::cluster.mbarrier::complete_tx::bytes.v4.b32 [%0], {%1,%2,%3,%4}, [%5];" :: "r"(a), "r"(x), "r"(y), "r"(z), "r"(w), "r"(bar) : "memory");
}
__device__ __forceinline__ void mbar_init(uint32_t b, uint32_t cnt) { asm volatile("mbarrier.init.shared::cta.b64 [%0], %1;" :: "r"(b), "r"(cnt) : "memory"); }
__device__ __forceinline__ void mbar_fence_init() { asm volatile("fence.mbarrier_init.release.cluster;" ::: "memory"); }
__device__ __forceinline__ void mbar_expect(uint32_t b, uint32_t bytes) { asm volatile("mbarrier.arrive.expect_tx.shared::cta.b64 _, [%0], %1;" :: "r"(b), "r"(bytes) : "memory"); }
__device__ __forceinline__ void mbar_arrive(uint32_t b) { asm volatile("mbarrier.arrive.shared::cta.b64 _, [%0];" :: "r"(b) : "memory"); }
__device__ __forceinline__ void mbar_wait(uint32_t b) {
    asm volatile("{ .reg .pred p; .reg .u32 n; mov.u32 n, 0;\n"
                 "W: mbarrier.try_wait.parity.shared::cta.b64 p, [%0], 0; @p bra D; add.u32 n, n, 1; setp.lt.u32 p, n, 4000000; @p bra W; trap;\n"
                 "D: }" :: "r"(b) : "memory");
}
__device__ __forceinline__ bool mbar_test(uint32_t b) {
    uint32_t d; asm volatile("{ .reg .pred p; mbarrier.test_wait.parity.shared::cta.b64 p, [%1], 0; selp.u32 %0, 1, 0, p; }" : "=r"(d) : "r"(b) : "memory"); return d;
}
__device__ __forceinline__ void tma2d(uint32_t dst, const CUtensorMap* m, int c0, int c1, uint32_t bar) {
    asm volatile("cp.async.bulk.tensor.2d.shared::cluster.global.mbarrier::complete_tx::bytes [%0], [%1, {%3, %4}], [%2];"
                 :: "r"(dst), "l"(m), "r"(bar), "r"(c0), "r"(c1) : "memory");
}
__device__ __forceinline__ void tma4d(uint32_t dst, const CUtensorMap* m, int c0, int c1, int c2, int c3, uint32_t bar) {
    asm volatile("cp.async.bulk.tensor.4d.shared::cluster.global.mbarrier::complete_tx::bytes [%0], [%1, {%3, %4, %5, %6}], [%2];"
                 :: "r"(dst), "l"(m), "r"(bar), "r"(c0), "r"(c1), "r"(c2), "r"(c3) : "memory");
}
__device__ __forceinline__ uint32_t mapa(uint32_t a, uint32_t rank) { uint32_t r; asm("mapa.shared::cluster.u32 %0, %1, %2;" : "=r"(r) : "r"(a), "r"(rank)); return r; }
__device__ __forceinline__ void prefetch_map(const CUtensorMap* m) { asm volatile("prefetch.tensormap [%0];" :: "l"(m) : "memory"); }
__device__ __forceinline__ void bar_sync(int id, int n) { asm volatile("bar.sync %0, %1;" :: "r"(id), "r"(n) : "memory"); }
__device__ __forceinline__ void bar_arrive(int id, int n) { asm volatile("bar.arrive %0, %1;" :: "r"(id), "r"(n) : "memory"); }
__device__ __forceinline__ void cluster_arrive_relaxed() { asm volatile("barrier.cluster.arrive.relaxed.aligned;" ::: "memory"); }
__device__ __forceinline__ void cluster_wait() { asm volatile("barrier.cluster.wait.aligned;" ::: "memory"); }
__device__ __forceinline__ uint32_t ld_rlx32(const void* p) { uint32_t v; asm volatile("ld.relaxed.gpu.global.u32 %0, [%1];" : "=r"(v) : "l"(p) : "memory"); return v; }
__device__ __forceinline__ uint4 ld_rlx128(const void* p) {
    uint4 v; asm volatile("ld.relaxed.gpu.global.v4.u32 {%0,%1,%2,%3}, [%4];" : "=r"(v.x), "=r"(v.y), "=r"(v.z), "=r"(v.w) : "l"(p) : "memory"); return v;
}
__device__ __forceinline__ void st_rlx32(void* p, uint32_t v) { asm volatile("st.relaxed.gpu.global.u32 [%0], %1;" :: "l"(p), "r"(v) : "memory"); }
__device__ __forceinline__ void st_pkt(void* p, uint32_t x, uint32_t y, uint32_t z, uint32_t w) {
    asm volatile("{ .reg .b64 lo, hi; .reg .b128 v; mov.b64 lo, {%1, %2}; mov.b64 hi, {%3, %4}; mov.b128 v, {lo, hi}; st.relaxed.gpu.global.b128 [%0], v; }"
                 :: "l"(p), "r"(x), "r"(y), "r"(z), "r"(w) : "memory");
}
__device__ __forceinline__ uint4 ld_pkt(const void* p) {
    uint4 r;
    asm volatile("{ .reg .b64 lo, hi; .reg .b128 v; ld.relaxed.gpu.global.b128 v, [%4]; mov.b128 {lo, hi}, v; mov.b64 {%0, %1}, lo; mov.b64 {%2, %3}, hi; }"
                 : "=r"(r.x), "=r"(r.y), "=r"(r.z), "=r"(r.w) : "l"(p) : "memory");
    return r;
}
__device__ __forceinline__ uint32_t tag_of(uint32_t ticket) { return ticket / NCTA % 3u + 1u; }
__device__ __forceinline__ uint2 ldg64(const void* p) { uint2 v; asm volatile("ld.global.nc.v2.u32 {%0,%1}, [%2];" : "=r"(v.x), "=r"(v.y) : "l"(p)); return v; }
__device__ __forceinline__ uint4 ldg128(const void* p) { uint4 v; asm volatile("ld.global.nc.v4.u32 {%0,%1,%2,%3}, [%4];" : "=r"(v.x), "=r"(v.y), "=r"(v.z), "=r"(v.w) : "l"(p)); return v; }
__device__ __forceinline__ uint32_t ldg16(const void* p) { uint32_t v; asm volatile("ld.global.nc.u16 %0, [%1];" : "=r"(v) : "l"(p)); return v; }
__device__ __forceinline__ uint32_t clk() { uint32_t t; asm volatile("mov.u32 %0, %clock;" : "=r"(t) :: "memory"); return t; }
__device__ __forceinline__ void spin_until(uint32_t t0, uint32_t d) { while (clk() - t0 < d) { } }
__device__ __forceinline__ float sigmoidf_(float x) { return __fdividef(1.0f, 1.0f + __expf(-x)); }
__device__ __forceinline__ int key_row(uint32_t key) { return 2047 - (int)(key & 2047u); }
__device__ __forceinline__ float key_val(uint32_t key) {
    const uint32_t o = key & 0xffff0000u; return __uint_as_float((o & 0x80000000u) ? (o & 0x7fffffffu) : (~o & 0xffff0000u));
}
#define POLL_GUARD(it) if (++(it) > (1 << 20)) __trap()

constexpr int UT_PL = 2240, UT_STRIDE = 4544;
constexpr int KT_P = 0, KT_P4 = 544 * 4, KT_P8 = KT_P4 + 184 * 4, KT_BYTES = KT_P8 + 144 * 4;
constexpr int KG_STAGE = 33 * 256;
constexpr int OUT_HALF = 2368, OUT_STAGE = 2 * OUT_HALF;
constexpr int SC_UTILE = 0;
constexpr int SC_UT = 32768;
constexpr int SC_KT = SC_UT + 8 * UT_STRIDE;
constexpr int SC_STG = SC_KT + 8 * KT_BYTES;
constexpr int SC_G = SC_STG + 8 * KG_STAGE;
constexpr int SC_OUT = SC_G + 8192;
constexpr int SC_BNC = SC_OUT + 8 * OUT_STAGE;
constexpr int SC_RED = SC_BNC + 2048;
constexpr int SC_MASK = SC_RED + 2048;
constexpr int SC_BAR = SC_MASK + 256;
constexpr int SC_END = SC_BAR + 256;
static_assert(SC_STG % 128 == 0 && SC_OUT % 128 == 0 && SC_KT % 16 == 0, "align");
constexpr int PIECE = 20480;
constexpr int SF_R = 9 * PIECE;
constexpr int SF_XS = SF_R + 36864;
constexpr int SF_LIST = SF_XS, SF_WR = SF_XS + 4096, SF_PART = SF_WR + 2304 + 16;
constexpr int SF_H = SF_XS + 9344;
constexpr int SF_BAR = SF_H + 1280;
constexpr int SF_MAX = SF_BAR + 192, SF_CNT = SF_MAX + 64, SF_TK = SF_CNT + 4, SF_SEL = SF_CNT + 16;
constexpr int SF_END = SF_SEL + 32;
constexpr int SM_TIM = SF_END;
constexpr int SMEM_BYTES = SF_END + 256;
static_assert(SMEM_BYTES <= 232448 && SC_END <= SF_END, "smem");

struct cplx { float re, im; };
struct h2c { __half2 re, im; };
__device__ __forceinline__ cplx csq(cplx a) { cplx r; r.re = a.re * a.re - a.im * a.im; r.im = (a.re * a.im) * 2.f; return r; }
__device__ __forceinline__ cplx cexp2(float x, float y) {
    float m; asm("ex2.approx.ftz.f32 %0, %1;" : "=f"(m) : "f"(x));
    cplx o; o.re = m * __cosf(y); o.im = m * __sinf(y); return o;
}
__device__ __forceinline__ h2c hpack(cplx a, cplx b) { h2c r; const uint32_t x = pack_f16(a.re, b.re), y = pack_f16(a.im, b.im); r.re = *(const __half2*)&x; r.im = *(const __half2*)&y; return r; }
__device__ __forceinline__ h2c hmulc(h2c a, h2c m) { h2c r; r.re = __hfma2(a.re, m.re, __hneg2(__hmul2(a.im, m.im))); r.im = __hfma2(a.re, m.im, __hmul2(a.im, m.re)); return r; }
__device__ __forceinline__ h2c hmulj(h2c a, h2c m) { h2c r; r.re = __hfma2(a.re, m.re, __hmul2(a.im, m.im)); r.im = __hfma2(a.im, m.re, __hneg2(__hmul2(a.re, m.im))); return r; }
__device__ __forceinline__ uint32_t hb(__half2 x) { return *(uint32_t*)&x; }
__device__ __forceinline__ h2c mk(uint32_t x, uint32_t y) { h2c r; r.re = *(__half2*)&x; r.im = *(__half2*)&y; return r; }

__device__ __forceinline__ void kgen(const uint2 (&v)[6], uint32_t logdt, uint32_t stage, uint32_t kt) {
    const int lane = threadIdx.x & 31, g = lane >> 2, t = lane & 3;
    if (lane < 27) {
        const int w = lane < 4 ? 4 * lane : lane < 15 ? 528 + 4 * (lane - 4) : 696 + 4 * (lane - 15);
        sts128(kt + 4 * w, 0, 0, 0, 0);
    }
    const uint32_t we = stage + lane * 8, wo = stage + ((lane * 8) ^ 64);
    sts64(we, 0x3c003c00u, 0u);
    const float dt = rbf(__expf(bf_lo(logdt)));
    cplx W[4];
#pragma unroll
    for (int i = 0; i < 4; i++) {
        auto val = [&](int k) { const uint32_t w = (i & 2) ? v[k].y : v[k].x; return (i & 1) ? bf_hi(w) : bf_lo(w); };
        const float br = val(2), bi = val(3), cr = val(4), ci = val(5);
        W[i].re = cr * br - ci * bi; W[i].im = cr * bi + ci * br;
    }
    float k0 = (W[0].re + W[1].re) + (W[2].re + W[3].re);
    const float mx = fmaxf(fmaxf(fmaxf(fabsf(W[0].re), fabsf(W[0].im)), fmaxf(fabsf(W[1].re), fabsf(W[1].im))), fmaxf(fmaxf(fabsf(W[2].re), fabsf(W[2].im)), fmaxf(fabsf(W[3].re), fabsf(W[3].im))));
    const uint32_t ex = max(__reduce_max_sync(0xffffffffu, __float_as_uint(mx)) >> 23, 10u);
    const float sc = __uint_as_float((263u - ex) << 23), fin = dt * __uint_as_float((ex - 9u) << 23);
#pragma unroll
    for (int o = 16; o; o >>= 1) k0 += __shfl_xor_sync(0xffffffffu, k0, o);
    const float dl = dt * 1.4426950408889634f;
    float acc[5][4];
#pragma unroll
    for (int a = 0; a < 5; a++) acc[a][0] = acc[a][1] = acc[a][2] = acc[a][3] = 0.f;
    uint32_t are = v[0].x, aim = v[1].x;
    cplx Wa = W[0], Wb = W[1];
    const uint32_t rd0 = stage + g * 256 + t * 16 + 64 * (g & 1), rd1 = rd0 ^ 64, rdm = stage + 32 * 256 + t * 16;
#pragma unroll 1
    for (int r = 0; r < 2; r++) {
        auto put = [&](int row, h2c x) { sts64(((row & 1) ? wo : we) + row * 256, hb(x.re), hb(x.im)); };
        const float xa = bf_lo(are) * dl, xb = bf_hi(are) * dl, ya = bf_lo(aim) * dt, yb = bf_hi(aim) * dt;
        cplx a = cexp2(xa, ya), b = cexp2(xb, yb), c = cexp2(64.f * xa, 64.f * ya), d = cexp2(64.f * xb, 64.f * yb);
        h2c c1;
        {
            cplx p, q; const float ar = a.re * sc, ai = a.im * sc, br = b.re * sc, bi = b.im * sc;
            p.re = Wa.re * ar - Wa.im * ai; p.im = -(Wa.re * ai) - Wa.im * ar; q.re = Wb.re * br - Wb.im * bi; q.im = -(Wb.re * bi) - Wb.im * br;
            c1 = hpack(p, q);
        }
        const h2c z1 = hpack(a, b); a = csq(a); b = csq(b);
        put(32, hpack(c, d)); c = csq(c); d = csq(d);
        const h2c z2 = hpack(a, b); a = csq(a); b = csq(b);
        const h2c z128 = hpack(c, d); c = csq(c); d = csq(d);
        const h2c z4 = hpack(a, b); a = csq(a); b = csq(b);
        const h2c z256 = hpack(c, d); c = csq(c); d = csq(d);
        const h2c z8 = hpack(a, b); a = csq(a); b = csq(b);
        const h2c z512 = hpack(c, d);
        const h2c z16 = hpack(a, b); a = csq(a); b = csq(b);
        const h2c z32 = hpack(a, b);
        const h2c c2 = hmulj(c1, z1), c3 = hmulj(c1, z2), c4 = hmulj(c2, z2), c6 = hmulj(c2, z4), c8 = hmulj(c4, z4);
        put(8, c1); put(9, c2); put(10, c3); put(11, c4); put(12, hmulj(c1, z4)); put(13, c6); put(14, hmulj(c3, z4)); put(15, c8);
        const h2c e260 = hmulj(c4, z256), e264 = hmulj(c8, z256), e520 = hmulj(c8, z512), e776 = hmulj(e264, z512);
        put(16, hmulj(c2, z256)); put(17, hmulj(c4, z512)); put(18, e260); put(19, e520); put(20, hmulj(c6, z256)); put(21, hmulj(e260, z512)); put(22, e264); put(23, e776);
        const h2c d0 = hmulj(e520, z512), d2 = hmulj(e776, z512), d4 = hmulj(d0, z512), d6 = hmulj(d2, z512);
        put(24, d0); put(25, d4); put(26, hmulj(d0, z128)); put(27, hmulj(d4, z128)); put(28, d2); put(29, d6); put(30, hmulj(d2, z128)); put(31, hmulj(d6, z128));
        const h2c z24 = hmulc(z8, z16);
        put(1, z8); put(2, z16); put(3, z24); put(4, z32); put(5, hmulc(z8, z32)); put(6, hmulc(z16, z32)); put(7, hmulc(z24, z32));
        __syncwarp();
#pragma unroll
        for (int s = 0; s < 4; s++) {
            const uint32_t rd = ((s & 1) ? rd1 : rd0) + 128 * (s >> 1);
            const uint4 A = lds128(rd), M = lds128(rdm + 64 * s), B0 = lds128(rd + 2048), B1 = lds128(rd + 4096), B2 = lds128(rd + 6144);
#pragma unroll
            for (int e = 0; e < 2; e++) {
                const h2c p0 = e ? mk(A.z, A.w) : mk(A.x, A.y), m = e ? mk(M.z, M.w) : mk(M.x, M.y);
                const h2c p1 = hmulc(p0, m), p2 = hmulc(p1, m), p3 = hmulc(p2, m);
                mma_f16(acc[0], hb(p0.re), hb(p1.re), hb(p0.im), hb(p1.im), e ? B0.z : B0.x, e ? B0.w : B0.y);
                mma_f16(acc[2], hb(p0.re), hb(p1.re), hb(p0.im), hb(p1.im), e ? B1.z : B1.x, e ? B1.w : B1.y);
                mma_f16(acc[4], hb(p0.re), hb(p1.re), hb(p0.im), hb(p1.im), e ? B2.z : B2.x, e ? B2.w : B2.y);
                mma_f16(acc[1], hb(p2.re), hb(p3.re), hb(p2.im), hb(p3.im), e ? B0.z : B0.x, e ? B0.w : B0.y);
                mma_f16(acc[3], hb(p2.re), hb(p3.re), hb(p2.im), hb(p3.im), e ? B1.z : B1.x, e ? B1.w : B1.y);
            }
        }
        __syncwarp();
        are = v[0].y; aim = v[1].y; Wa = W[2]; Wb = W[3];
    }
#pragma unroll
    for (int a = 0; a < 5; a++) { acc[a][0] *= fin; acc[a][1] *= fin; acc[a][2] *= fin; acc[a][3] *= fin; }
    float carry = k0 * dt;
    if (lane == 0) sts32(kt + KT_P + 15 * 4, pack_bf16(carry, 0.f));
#pragma unroll
    for (int q = 0; q < 8; q++) {
        const float hi = q < 4 ? acc[q >> 1][2 * (q & 1) + 1] : acc[q >> 1][2 * (q & 1)];
        const float sh = __shfl_sync(0xffffffffu, hi, (lane + 31) & 31);
        const float prev = lane ? sh : carry;
        carry = sh;
        const float lo = q < 4 ? acc[q >> 1][2 * (q & 1)] : ((lane & 1) ? hi : prev);
        sts64(kt + KT_P + (64 * q + 16) * 4 + lane * 8, pack_bf16(lo, prev), pack_bf16(hi, lo));
    }
    if (lane == 0) { const uint32_t w = pack_bf16(carry, carry); sts128(kt + KT_P + 528 * 4, w, w, w & 0xffff0000u, 0u); }
    const uint32_t a4 = kt + KT_P4 + (24 + 2 * g + (t & 1) + 64 * (t >> 1)) * 4, a8 = kt + KT_P8 + (12 + 16 * t + g) * 4;
#pragma unroll
    for (int q = 0; q < 4; q++) {
        const uint32_t x = pack_bf16(acc[2 + (q >> 1)][2 * (q & 1) + 1], 0.f), y = pack_bf16(acc[4][q], 0.f);
        sts16(a4 + 64 * q, x); sts16(a4 + 64 * q + 18, x);
        sts16(a8 + 256 * (q & 1) + 32 * (q >> 1), y); sts16(a8 + 256 * (q & 1) + 32 * (q >> 1) + 10, y);
    }
    __syncwarp();
}

__device__ __forceinline__ uint32_t band(int e, int c, int h) {
    return (((unsigned)(e - c + h) <= 2u * h) ? 0x3f80u : 0u) | (((unsigned)(e + 1 - c + h) <= 2u * h) ? 0x3f800000u : 0u);
}

__device__ __forceinline__ void conv_warp(const Params& p, uint32_t sb, int cb) {
    const int warp = threadIdx.x >> 5, lane = threadIdx.x & 31, g = lane >> 2, t = lane & 3, mi = lane >> 3, r8 = lane & 7;
    const int rank = cb & 1, ch = 8 * cb + warp;
    const uint32_t kt = sb + SC_KT + warp * KT_BYTES, ut = sb + SC_UT + warp * UT_STRIDE + 128;
    const uint32_t bar_ut = sb + SC_BAR + 32, bar_out = sb + SC_BAR + 48, bar_g = sb + SC_BAR + 112;
    uint32_t dsk;
    {
        uint2 v[6];
        const int o = ch * NST + 4 * lane;
        v[0] = ldg64(p.Are + o); v[1] = ldg64(p.Aim + o); v[2] = ldg64(p.Bre + o); v[3] = ldg64(p.Bim + o); v[4] = ldg64(p.Cre + o); v[5] = ldg64(p.Cim + o);
        const uint32_t logdt = ldg16(p.logdt + ch);
        dsk = ldg16(p.Dskip + ch);
        if (lane < 16) sts128(ut - 128 + (lane >> 3) * UT_PL + r8 * 16, 0, 0, 0, 0);
        kgen(v, logdt, sb + SC_STG + warp * KG_STAGE, kt);
    }
    TSTAMP(32 + warp);
    cluster_wait();
    float acc[16][4];
    const int d0 = g - 2 * t;
    const uint32_t oz = blockIdx.y;
    {
        uint32_t kb[8][2];
#pragma unroll
        for (int l = 0; l < 8; l++) { const uint2 x = lds64(kt + KT_P8 + (6 + 8 * l + d0) * 8); kb[l][0] = x.x; kb[l][1] = x.y; }
        const uint32_t w0 = band(4 * t, 4 + g, 4), w1 = band(4 * t, 4 + g, 3), w2 = band(4 * t + 2, 4 + g, 4), w3 = band(4 * t + 2, 4 + g, 3);
        const uint32_t a0 = ut + g * 16 + (t == 0 ? UT_PL - 8 : t == 3 ? UT_PL : 8 * (t - 1));
        const uint32_t a1 = ut + g * 16 + (t == 0 ? -8 : t == 3 ? 0 : UT_PL - 16 + 8 * (t - 1));
        mbar_wait(bar_ut);
        if (warp == 0) TSTAMP(2);
#pragma unroll
        for (int j = 0; j < 8; j++) {
            const uint2 x = lds64(a0 + 128 * j - 16), y = lds64(a1 + 128 * j), z = lds64(a0 + 128 * j);
            float X[4], Y[4], Z[4];
            mma_bf0(X, w0, w1, w2, w3, x.x, x.y); mma_bf0(Y, w0, w1, w2, w3, y.x, y.y); mma_bf0(Z, w0, w1, w2, w3, z.x, z.y);
            const uint32_t q0 = pack_bf16(Y[2], Y[3]), q1 = pack_bf16(Z[2], Z[3]), q2 = pack_bf16(X[0], X[1]), q3 = pack_bf16(Y[0], Y[1]);
#pragma unroll
            for (int l = 0; l < 8 - j; l++) {
                if (j == 0) mma_bf0(acc[8 + l], q0, q1, q2, q3, kb[l][0], kb[l][1]);
                else mma_bf(acc[8 + j + l], q0, q1, q2, q3, kb[l][0], kb[l][1]);
            }
        }
    }
    TSTAMP(40 + warp);
    const uint32_t ub = ut + (mi & 1) * UT_PL + (mi >> 1) * 128 + r8 * 16;
    const uint32_t kp = kt + KT_P + (15 + d0) * 4;
    mbar_wait(bar_ut + 8);
    {
        const uint32_t c0 = lds32(kp + 512 * 4), c1 = lds32(kp + 520 * 4), c2 = lds32(kp + 504 * 4);
        const uint32_t kv = __byte_perm(lds32(kt + KT_P4 + 151 * 4), 0, 0x1010);
        const uint32_t e0 = kv & ((((unsigned)(d0 - 3) < 2u) ? 0xffffu : 0u) | (((unsigned)(d0 - 4) < 2u) ? 0xffff0000u : 0u));
        const uint32_t e1 = kv & ((((unsigned)(d0 + 5) < 2u) ? 0xffffu : 0u) | (((unsigned)(d0 + 4) < 2u) ? 0xffff0000u : 0u));
        const uint32_t c3 = c0 + oz, c4 = c1 + oz, e3 = e0 + oz, e4 = e1 + oz, z1 = oz + oz, z2 = oz * 3u;
        const uint32_t uf = ut + UT_PL - 16 + mi * 128 + r8 * 16;
#pragma unroll
        for (int i = 0; i < 4; i++) acc[i][0] = acc[i][1] = acc[i][2] = acc[i][3] = 0.f;
#pragma unroll
        for (int m4 = 0; m4 < 3; m4++) {
            uint32_t b[2][4], f[4];
            ldsm4(b[0], ub + 512 * m4); ldsm4(b[1], ub + 512 * m4 + 256); ldsm4(f, uf + 512 * m4);
#pragma unroll
            for (int k = 0; k < 4; k++) {
                if (m4 == 0) mma_bf0(acc[4 + k], c0, c1, c2, c3, b[k >> 1][2 * (k & 1)], b[k >> 1][2 * (k & 1) + 1]);
                else mma_bf(acc[4 * m4 + 4 + k], c0, c1, c2, c3, b[k >> 1][2 * (k & 1)], b[k >> 1][2 * (k & 1) + 1]);
            }
            if (m4 < 2) {
#pragma unroll
                for (int k = 0; k < 4; k++) mma_bf(acc[4 * m4 + 8 + k], e0, e1, oz, e3, b[k >> 1][2 * (k & 1)], b[k >> 1][2 * (k & 1) + 1]);
            }
#pragma unroll
            for (int k = 0; k < 4; k++) mma_bf8(acc[4 * m4 + 4 + k], c4, z1, f[k]);
            if (m4 < 2) {
#pragma unroll
                for (int k = 0; k < 4; k++) mma_bf8(acc[4 * m4 + 8 + k], e4, z2, f[k]);
            }
        }
    }
#pragma unroll 1
    for (int j0 = 0; j0 < 8; j0++) {
        uint32_t a[4][4];
        const uint32_t k1 = kp + 64 * j0, u1 = ub - 16 * j0;
#pragma unroll
        for (int j1 = 0; j1 < 4; j1++) { a[j1][0] = lds32(k1 + 512 * j1); a[j1][1] = lds32(k1 + 512 * j1 + 32); a[j1][2] = lds32(k1 + 512 * j1 - 32); a[j1][3] = a[j1][0] + oz; }
#pragma unroll
        for (int m2 = 0; m2 < 8; m2++) {
            uint32_t b[4];
            ldsm4(b, u1 + 256 * m2);
#pragma unroll
            for (int e = 0; e < 2; e++)
#pragma unroll
                for (int j1 = 0; j1 < 4; j1++)
                    if (2 * m2 + e + j1 < 16) mma_bf(acc[2 * m2 + e + j1], a[j1][0], a[j1][1], a[j1][2], a[j1][3], b[2 * e], b[2 * e + 1]);
        }
    }
    TSTAMP(48 + warp);
    uint32_t kb[5][4];
#pragma unroll
    for (int l = 0; l < 5; l++) { const uint4 x = lds128(kt + KT_P4 + (6 + 8 * l + d0) * 16); kb[l][0] = x.x; kb[l][1] = x.y; kb[l][2] = x.z; kb[l][3] = x.w; }
    const uint32_t w0 = band(2 * t, 2 + g, 2), w1 = band(2 * t, 6 + g, 1), w2 = band(2 * t + 8, 2 + g, 2), w3 = band(2 * t + 8, 6 + g, 1);
    const uint32_t a0 = ut + g * 16 + (t == 0 ? UT_PL - 4 : 4 * (t - 1)), a1 = ut + g * 16 + (t == 0 ? 12 : UT_PL + 4 * (t - 1));
    const uint32_t D2 = __byte_perm(dsk, 0, 0x1010);
    const uint32_t gb = sb + SC_G + (mi & 1) * 2048 + (mi >> 1) * 128 + r8 * 16;
    const bool mine = (mi >> 1) == rank;
    const uint32_t orow = sb + SC_OUT + rank * OUT_HALF + warp * 288, bnc = sb + SC_BNC + warp * 256;
    const uint32_t ow = (mine ? orow : bnc) + (mi & 1) * 128 + r8 * 16, ostep = mine ? OUT_STAGE : 0;
    const uint32_t rem = mapa(orow + lane * 8, rank ^ 1), rbar = mapa(bar_out, rank ^ 1);
    const uint32_t ord = sb + SC_OUT + ((r8 >> 1) & 1) * OUT_HALF + (2 * mi + (r8 & 1)) * 288 + (2 * warp + (r8 >> 2)) * 16;
    const int pos = 2 * warp + (t >> 1), roff = 128 * rank + 16 * (pos & 7) + 8 * (pos >> 3) + g;
    __nv_bfloat16* op = p.out + roff * DM + 16 * (cb >> 1) + 8 * (t & 1);
    mbar_wait(bar_g);
    const uint32_t skip = lds8(sb + SC_MASK + roff);
    auto emit = [&](int q) {
        uint32_t u4[4], g4[4], o4[4], r[4];
        ldsm4t(u4, ub + 256 * q); ldsm4t(g4, gb + 256 * q); ldsm4t(o4, gb + 4096 + 256 * q);
#pragma unroll
        for (int k = 0; k < 4; k++) {
            const uint32_t y = pack_bf16(acc[2 * q + (k >> 1)][2 * (k & 1)], acc[2 * q + (k >> 1)][2 * (k & 1) + 1]);
            r[k] = hadd2(hmul2(g4[k], hadd2(y, hmul2(u4[k], D2))), hmul2(o4[k], u4[k]));
        }
        stsm4t(ow + q * ostep, r[0], r[1], r[2], r[3]);
        __syncwarp();
        const uint2 x = lds64(bnc + lane * 8);
        if (lane == 0) mbar_arrive(bar_out + 8 * q);
        st_async64(rem + q * OUT_STAGE, x.x, x.y, rbar + 8 * q);
        __syncwarp();
    };
    auto store = [&](int q) {
        uint32_t r[4];
        mbar_wait(bar_out + 8 * q);
        ldsm4t(r, ord + q * OUT_STAGE);
        if (!((skip >> q) & 1)) *(uint4*)(op + q * 256 * DM) = make_uint4(r[0], r[1], r[2], r[3]);
    };
    emit(0); emit(1);
#pragma unroll
    for (int j = 0; j < 12; j++) {
        const uint32_t x0 = lds32(a0 + 128 * j - 16), x1 = lds32(a1 + 128 * j - 16), x2 = lds32(a0 + 128 * j), x3 = lds32(a1 + 128 * j);
        float X[4], Y[4], Z[4];
        mma_bf0(X, w0, w1, w2, w3, x0, x1); mma_bf0(Y, w0, w1, w2, w3, x1 + oz, x2 + oz); mma_bf0(Z, w0, w1, w2, w3, x2, x3);
        const uint32_t x5 = pack_bf16(X[0], X[1]), xw3 = pack_bf16(X[2], X[3]), y5 = pack_bf16(Y[0], Y[1]), y3 = pack_bf16(Y[2], Y[3]), z5 = pack_bf16(Z[0], Z[1]), z3 = pack_bf16(Z[2], Z[3]);
        const uint32_t y3c = y3 + oz, y5c = y5 + oz;
#pragma unroll
        for (int l = 0; l < 5; l++) if (j + 4 + l < 16) mma_bf(acc[j + 4 + l], y3, z3, y5, z5, kb[l][0], kb[l][1]);
#pragma unroll
        for (int l = 0; l < 5; l++) if (j + 4 + l < 16) mma_bf(acc[j + 4 + l], xw3, y3c, x5, y5c, kb[l][2], kb[l][3]);
        if (j & 1) { emit(2 + (j >> 1)); store(j >> 1); }
    }
    TSTAMP(56 + warp);
    store(6); store(7);
    if (warp == 0) TSTAMP(6);
}

__device__ __forceinline__ void conv_helper(const Params& p, const CUtensorMap* mU, uint32_t sb, int cb, uint32_t t0) {
    const int hw = (threadIdx.x >> 5) - 8, lane = threadIdx.x & 31, g = lane >> 2, t = lane & 3, mi = lane >> 3, r8 = lane & 7, ht = threadIdx.x - 256;
    const int rank = cb & 1, slab = cb >> 1;
    const uint32_t bar_box = sb + SC_BAR + 8 * hw, bar_ut = sb + SC_BAR + 32, bar_out = sb + SC_BAR + 48, bar_g = sb + SC_BAR + 112, s_tk = sb + SC_BAR + 120;
    if (lane == 0) {
        mbar_init(bar_box, 1);
        mbar_fence_init();
        mbar_expect(bar_box, 8192);
        if (UDELAY) spin_until(t0, UDELAY);
        tma4d(sb + SC_UTILE + hw * 8192, mU, 16 * slab, 0, 32 * hw + 16 * rank, 0, bar_box);
        mbar_init(bar_out + 16 * hw, 9); mbar_init(bar_out + 16 * hw + 8, 9);
        if (hw < 2) mbar_init(bar_ut + 8 * hw, 3); else if (hw == 2) mbar_init(bar_g, 4);
        mbar_fence_init();
        mbar_expect(bar_out + 16 * hw, 2048); mbar_expect(bar_out + 16 * hw + 8, 2048);
        if (hw < 2) mbar_expect(bar_ut + 8 * hw, 8192);
    }
    __syncwarp();
    cluster_arrive_relaxed();
    if (ht == 96) sts32(s_tk, atomicAdd(&p.scr->launch, 1u));
    if (ht < 64) sts32(sb + SC_MASK + ht * 4, 0);
    cluster_wait();
    {
        const uint32_t src = sb + SC_UTILE + hw * 8192 + (32 * mi + r8) * 32;
        const uint32_t so = (rank ^ (r8 >> 2)) << 4;
        const uint32_t dst = sb + SC_UT + g * UT_STRIDE + 128 + (32 * hw + 16 * rank + t) * 16;
        const uint32_t rdst = mapa(dst, rank ^ 1), rbar = mapa(bar_ut + 8 * (hw >> 1), rank ^ 1);
        mbar_wait(bar_box);
        if (hw == 0) TSTAMP(8); if (hw == 3) TSTAMP(9);
#pragma unroll
        for (int h = 0; h < 2; h++) {
            uint32_t a[4][4], b[4][4];
#pragma unroll
            for (int k = 0; k < 4; k++) { ldsm4t(a[k], src + (so ^ 16) + h * 4096 + k * 256); ldsm4t(b[k], src + so + h * 4096 + k * 256); }
#pragma unroll
            for (int k = 0; k < 4; k++) {
                st_async128(rdst + h * UT_PL + k * 64, a[k][0], a[k][1], a[k][2], a[k][3], rbar);
                sts128(dst + h * UT_PL + k * 64, b[k][0], b[k][1], b[k][2], b[k][3]);
            }
        }
        __syncwarp();
        if (lane == 0) mbar_arrive(bar_ut + 8 * (hw >> 1));
    }
    bar_sync(1, 128);
    const uint32_t tag = tag_of(lds32(s_tk));
    uint32_t key;
    for (int it = 0;;) {
        key = ld_rlx32(&p.scr->sel[ht >> 4]);
        if (__all_sync(0xffffffffu, ((key >> 11) & 3u) == tag)) break;
        POLL_GUARD(it);
        __nanosleep(200);
    }
    if (hw == 0) TSTAMP(10);
    const int row = key_row(key), c = ht & 15;
    const uint32_t xv = ldg16(p.u + row * DM + 16 * slab + c);
#pragma unroll 1
    for (int k = 0; k < 2; k++) {
        const int chunk = ht + 128 * k;
        uint4 a, b;
        const uint32_t tg = tag << 14;
        for (int it = 0;;) {
            a = ld_rlx128(&p.scr->rec[8 * chunk]); b = ld_rlx128(&p.scr->rec[8 * chunk + 4]);
            if ((((a.x ^ tg) | (a.y ^ tg) | (a.z ^ tg) | (a.w ^ tg) | (b.x ^ tg) | (b.y ^ tg) | (b.z ^ tg) | (b.w ^ tg)) & 0xc000u) == 0) break;
            POLL_GUARD(it);
        }
        const uint32_t g0 = __byte_perm(a.x, a.y, 0x5410) & 0x3fff3fffu, g1 = __byte_perm(a.z, a.w, 0x5410) & 0x3fff3fffu;
        const uint32_t g2 = __byte_perm(b.x, b.y, 0x5410) & 0x3fff3fffu, g3 = __byte_perm(b.z, b.w, 0x5410) & 0x3fff3fffu;
        const uint32_t d = sb + SC_G + (chunk & 1) * 2048 + (chunk >> 1) * 16;
        sts128(d, g0, g1, g2, g3);
        sts128(d + 4096, hsub2(0x3f803f80u, g0), hsub2(0x3f803f80u, g1), hsub2(0x3f803f80u, g2), hsub2(0x3f803f80u, g3));
    }
    bar_sync(1, 128);
    const uint32_t oma = sb + SC_G + 4096 + ((row >> 3) & 1) * 2048 + (row >> 4) * 16 + (row & 7) * 2;
    const float om = bf_lo(lds16(oma));
    __syncwarp();
    if (c == 0) {
        sts16(oma, 0);
        asm volatile("red.shared.or.b32 [%0], %1;" :: "r"(sb + SC_MASK + (row & 252)), "r"(1u << (8 * (row & 3) + (row >> 8))) : "memory");
    }
    __syncwarp();
    if (lane == 0) mbar_arrive(bar_g);
    if (hw == 0) TSTAMP(11);
    const float rs = rbf(sigmoidf_(key_val(key)));
    const uint4* src = p.scr->part + (slab * NFFN + 15 * hw) * 32;
    for (int it = 0;;) {
        const uint32_t w = ld_rlx32(src + min(lane, 14) * 32);
        if (__any_sync(0xffffffffu, (w & 3u) == tag)) break;
        POLL_GUARD(it);
        __nanosleep(100);
    }
    if (hw == 0) TSTAMP(12);
    uint4 v[15];
#pragma unroll
    for (int k = 0; k < 15; k++) v[k].x = 0;
    for (int it = 0;;) {
#pragma unroll
        for (int k = 0; k < 15; k++) if ((v[k].x & 3u) != tag) v[k] = ld_pkt(src + k * 32 + lane);
        uint32_t bad = 0;
#pragma unroll
        for (int k = 0; k < 15; k++) bad |= v[k].x ^ tag;
        if (__all_sync(0xffffffffu, (bad & 3u) == 0)) break;
        POLL_GUARD(it);
    }
    float s0 = 0.f, s1 = 0.f, s2 = 0.f, s3 = 0.f;
#pragma unroll
    for (int k = 0; k < 15; k++) { s0 += __uint_as_float(v[k].x); s1 += __uint_as_float(v[k].y); s2 += __uint_as_float(v[k].z); s3 += __uint_as_float(v[k].w); }
    sts128(sb + SC_RED + ht * 16, __float_as_uint(s0), __float_as_uint(s1), __float_as_uint(s2), __float_as_uint(s3));
    bar_sync(1, 128);
    if (hw == 0) TSTAMP(13);
    if (((row >> 7) & 1) == rank) {
        const int tok = ht >> 4;
        const uint32_t ra = sb + SC_RED + ((c & 7) * 4 + (tok >> 1)) * 16 + ((c >> 3) * 2 + (tok & 1)) * 4;
        const float y = rbf((__uint_as_float(lds32(ra)) + __uint_as_float(lds32(ra + 512))) + (__uint_as_float(lds32(ra + 1024)) + __uint_as_float(lds32(ra + 1536))));
        const float b = rbf(bf_lo(xv) + rbf(y * rs));
        mbar_wait(bar_out + 8 * (row >> 8));
        const float ga = bf_lo(lds16(sb + SC_OUT + (row >> 8) * OUT_STAGE + (c >> 3) * OUT_HALF + (c & 7) * 288 + (((row >> 4) & 7) + (row & 8)) * 16 + (row & 7) * 2));
        *(unsigned short*)(p.out + row * DM + 16 * slab + c) = (unsigned short)pack_bf16(ga + rbf(om * b), 0.f);
    }
    if (hw == 0) TSTAMP(14);
}

__device__ __forceinline__ void ffn_cta(const Params& p, const CUtensorMap* mR, const CUtensorMap* mG64, const CUtensorMap* mU64, const CUtensorMap* mG16,
                                        const CUtensorMap* mU16, const CUtensorMap* mWd, uint32_t sb, int f, uint32_t t0) {
    const int tid = threadIdx.x, warp = tid >> 5, lane = tid & 31, g = lane >> 2, t = lane & 3, mi = lane >> 3, r8 = lane & 7;
    const bool wide = f < 48;
    const int nunit = wide ? 10 : 8;
    const uint32_t bar_w = sb + SF_BAR, bar_d = bar_w + 72, bar_r = bar_w + 112, bar_sel = bar_w + 152, bar_free = bar_w + 160;
    uint32_t tag;
    uint4* const pdst = p.scr->part + (3 * warp * NFFN + f) * 32 + lane;
    auto clear_part = [&]() { st_pkt(pdst, 0, 0, 0, 0); st_pkt(pdst + NFFN * 32, 0, 0, 0, 0); st_pkt(pdst + 2 * NFFN * 32, 0, 0, 0, 0); };
    if (warp == 11) {
        if (lane == 0) {
            prefetch_map(mG64); prefetch_map(mU64); prefetch_map(mG16); prefetch_map(mU16); prefetch_map(mWd);
#pragma unroll 1
            for (int i = 0; i < 14; i++) mbar_init(bar_w + 8 * i, 1);
            mbar_init(bar_sel, f >= 44 ? 5 : 4); mbar_init(bar_free, nunit); mbar_init(bar_free + 8, nunit); mbar_init(bar_free + 16, nunit);
            mbar_fence_init();
        }
        __syncwarp();
        bar_arrive(1, NTHR);
        clear_part();
        if (lane == 0) {
            spin_until(t0, WDELAY);
#pragma unroll 1
            for (int n = 0; n < 9; n++) {
                if (n >= WWIN) { int it = 0; while (!mbar_test(bar_w + 8 * (n - WWIN)) && !mbar_test(bar_free)) POLL_GUARD(it); }
                if (n == 8) mbar_wait(bar_sel);
                const uint32_t b = bar_w + 8 * n, d = sb + n * PIECE;
                mbar_expect(b, wide ? PIECE : 16384);
                tma2d(d, mG64, 64 * f, 64 * n, b); tma2d(d + 8192, mU64, 64 * f, 64 * n, b);
                if (wide) { tma2d(d + 16384, mG16, 3840 + 16 * f, 64 * n, b); tma2d(d + 18432, mU16, 3840 + 16 * f, 64 * n, b); }
            }
            TSTAMP(10);
#pragma unroll 1
            for (int i = 0; i < nunit / 2; i++) {
                if (i < 2) { int it = 0; while (!mbar_test(bar_w + 8 * (9 + i - WWIN)) && !mbar_test(bar_free)) POLL_GUARD(it); }
                else mbar_wait(bar_free + 8 * (i - 2));
                mbar_expect(bar_d + 8 * i, 18432);
                tma2d(i < 2 ? sb + SF_R + i * 18432 : sb + (i - 2) * PIECE, mWd, 0, 9 * (i < 4 ? 64 * f + 16 * i : 3840 + 16 * f), bar_d + 8 * i);
            }
            TSTAMP(11);
        }
        __syncwarp();
    } else {
        const int ng = f >= 44 ? 5 : 4, r0 = f >= 44 ? 1408 + 40 * (f - 44) : 32 * f;
        const int grp = warp >> 1, kh = warp & 1;
        const uint32_t rows = grp < 4 ? sb + SF_R + grp * 9216 : sb + 8 * PIECE;
        if (kh == 0 && grp < ng && t == 0) st_rlx32(&p.scr->rec[r0 + 8 * grp + g], 0);
        if (f == 0 && tid < 8) st_rlx32(&p.scr->sel[tid], 0);
        if (lane == 0 && kh == 0 && grp < ng) {
            mbar_init(bar_r + 8 * grp, 1);
            mbar_fence_init();
            mbar_expect(bar_r + 8 * grp, 9216);
            spin_until(t0, RDELAY);
            tma2d(rows, mR, 0, 9 * (r0 + 8 * grp), bar_r + 8 * grp);
        }
        if (kh == 1) {
            const int i = 32 * grp + lane;
            if (i < 144) { const uint4 w = ldg128((const uint4*)(i < 72 ? p.wr : p.gatew - DM) + i); sts128(sb + SF_WR + i * 16, w.x, w.y, w.z, w.w); }
        }
        if (warp == 10) {
#pragma unroll 1
            for (int i = lane; i < 256; i += 32) sts128(sb + SF_LIST + i * 16, 0, 0, 0, 0);
            if (lane == 0) sts64(sb + SF_CNT, 0, atomicAdd(&p.scr->launch, 1u));
        }
        bar_sync(1, NTHR);
        tag = tag_of(lds32(sb + SF_TK));
        clear_part();
        if (grp < ng) {
            uint32_t wr[10][2], gw[9][4];
            const uint32_t wa = sb + SF_WR + kh * 576 + (2 * mi + (r8 & 1)) * 16, ga = sb + SF_WR + 1152 + kh * 576 + mi * 16;
#pragma unroll
            for (int i = 0; i < 5; i++) { uint32_t x[4]; ldsm4(x, wa + 128 * i); wr[2 * i][0] = x[0]; wr[2 * i][1] = x[1]; wr[2 * i + 1][0] = x[2]; wr[2 * i + 1][1] = x[3]; }
#pragma unroll
            for (int i = 0; i < 9; i++) ldsm4(gw[i], ga + 64 * i);
            float cr[4] = {0.f, 0.f, 0.f, 0.f}, cg[4] = {0.f, 0.f, 0.f, 0.f};
            mbar_wait(bar_r + 8 * grp);
            if (warp == 0) TSTAMP(1);
#pragma unroll
            for (int i = 0; i < 9; i++) {
                const int c = 36 * kh + 4 * i + mi, line = 9 * r8 + (c >> 3);
                uint32_t a[4];
                ldsm4(a, rows + line * 128 + (((c ^ line) & 7) << 4));
                mma_bf(cr, a[0], a[1], a[2], a[3], wr[i][0], wr[i][1]);
                mma_bf(cg, hmul2(a[0], gw[i][0]), hmul2(a[1], gw[i][1]), hmul2(a[2], gw[i][2]), hmul2(a[3], gw[i][3]), 0x3f803f80u, 0x3f803f80u);
            }
            const float sr = cr[0] + cr[3], sg = cg[0] + cg[2];
            if (kh == 1) {
                if (t == 0) sts64(sb + SF_PART + (grp * 8 + g) * 8, __float_as_uint(sr), __float_as_uint(sg));
                bar_arrive(2 + grp, 64);
            } else {
                bar_sync(2 + grp, 64);
                if (t == 0) {
                    const uint2 o = lds64(sb + SF_PART + (grp * 8 + g) * 8);
                    const uint32_t gg = pack_bf16(sigmoidf_(rbf(sg + __uint_as_float(o.y))), 0.f);
                    uint32_t rb = pack_bf16(0.f, sr + __uint_as_float(o.x));
                    rb = (rb & 0x80000000u) ? ~rb : (rb | 0x80000000u);
                    st_rlx32(&p.scr->rec[r0 + 8 * grp + g], (rb & 0xffff0000u) | (tag << 14) | (gg & 0x3fffu));
                }
                if (lane == 0) mbar_arrive(bar_sel);
                if (warp == 0) TSTAMP(2);
            }
        }
        if (warp < 8) {
            uint32_t k[8];
            const uint32_t tg = tag << 14;
            mbar_wait(bar_sel);
            spin_until(clk(), PDELAY);
            for (int it = 0;;) {
                const uint4 a = ld_rlx128(&p.scr->rec[4 * tid]), b = ld_rlx128(&p.scr->rec[1024 + 4 * tid]);
                k[0] = a.x; k[1] = a.y; k[2] = a.z; k[3] = a.w; k[4] = b.x; k[5] = b.y; k[6] = b.z; k[7] = b.w;
                if (__all_sync(0xffffffffu, (((a.x ^ tg) | (a.y ^ tg) | (a.z ^ tg) | (a.w ^ tg) | (b.x ^ tg) | (b.y ^ tg) | (b.z ^ tg) | (b.w ^ tg)) & 0xc000u) == 0)) break;
                POLL_GUARD(it);
            }
            if (warp == 0) TSTAMP(3);
#pragma unroll
            for (int i = 0; i < 8; i++) k[i] = (k[i] & 0xffff0000u) | (uint32_t)(2047 - 1024 * (i >> 2) - (i & 3) - 4 * tid);
            const uint32_t m0 = __reduce_max_sync(0xffffffffu, max(max(k[0], k[1]), max(k[2], k[3]))), m1 = __reduce_max_sync(0xffffffffu, max(max(k[4], k[5]), max(k[6], k[7])));
            if (lane == 0) sts64(sb + SF_MAX + warp * 8, m0, m1);
            bar_sync(7, 256);
            uint32_t thr;
            {
                const uint32_t m = lds32(sb + SF_MAX + (lane & 15) * 4);
                int rk = 0;
#pragma unroll
                for (int i = 0; i < 4; i++) { const uint4 x = lds128(sb + SF_MAX + 16 * i); rk += (x.x > m) + (x.y > m) + (x.z > m) + (x.w > m); }
                thr = __reduce_max_sync(0xffffffffu, rk == 7 ? m : 0u);
            }
#pragma unroll
            for (int i = 0; i < 8; i++)
                if (k[i] >= thr) { uint32_t s; asm volatile("atom.shared.add.u32 %0, [%1], 1;" : "=r"(s) : "r"(sb + SF_CNT) : "memory"); sts32(sb + SF_LIST + 4 * s, k[i]); }
            bar_sync(7, 256);
            const int n = lds32(sb + SF_CNT);
            uint32_t key = 0;
#pragma unroll 1
            for (int base = 0; base < n; base += 32) {
                const uint32_t m = lds32(sb + SF_LIST + (base + lane) * 4);
                int rk = 0;
#pragma unroll 1
                for (int i = 0; i < n; i += 8) {
                    const uint4 x = lds128(sb + SF_LIST + 4 * i), y = lds128(sb + SF_LIST + 4 * i + 16);
                    rk += (x.x > m) + (x.y > m) + (x.z > m) + (x.w > m) + (y.x > m) + (y.y > m) + (y.z > m) + (y.w > m);
                }
                if (rk == warp && base + lane < n) key = m;
            }
            key = __reduce_max_sync(0xffffffffu, key);
            if (warp == 0) TSTAMP(4);
            const uint4* xr = (const uint4*)(p.u + key_row(key) * DM);
            const uint4 x0 = ldg128(xr + lane), x1 = ldg128(xr + 32 + lane), x2 = ldg128(xr + 64 + r8);
            if (lane == 0) sts32(sb + SF_SEL + warp * 4, key | (tag << 11));
            bar_sync(7, 256);
            if (f == 0 && tid < 8) st_rlx32(&p.scr->sel[tid], lds32(sb + SF_SEL + tid * 4));
            const uint32_t xd = sb + SF_XS + warp * 1168 + lane * 16;
            sts128(xd, x0.x, x0.y, x0.z, x0.w); sts128(xd + 512, x1.x, x1.y, x1.z, x1.w);
            if (lane < 8) sts128(xd + 1024, x2.x, x2.y, x2.z, x2.w);
        }
        if (warp < nunit) {
            bar_sync(8, 32 * nunit);
            if (warp == 0) TSTAMP(5);
            const int kr = 8 * (mi >> 1) + r8;
            uint32_t wa = warp < 8 ? sb + (mi & 1) * 8192 + kr * 128 + ((warp ^ r8) << 4) : sb + 16384 + (mi & 1) * 2048 + kr * 32 + (((warp ^ (r8 >> 2)) & 1) << 4);
            const uint32_t ws = warp < 8 ? 2048 : 512;
            uint32_t xa = sb + SF_XS + r8 * 1168 + mi * 16;
            float c0[4] = {0.f, 0.f, 0.f, 0.f}, c1[4] = {0.f, 0.f, 0.f, 0.f};
#pragma unroll 1
            for (int n = 0; n < 9; n++) {
                uint32_t x[2][4], a[4][4];
                ldsm4(x[0], xa); ldsm4(x[1], xa + 64);
                mbar_wait(bar_w + 8 * n);
#pragma unroll
                for (int s = 0; s < 4; s++) ldsm4t(a[s], wa + s * ws);
                mma_bf(c0, a[0][0], a[0][1], a[0][2], a[0][3], x[0][0], x[0][1]);
                mma_bf(c1, a[1][0], a[1][1], a[1][2], a[1][3], x[0][2], x[0][3]);
                mma_bf(c0, a[2][0], a[2][1], a[2][2], a[2][3], x[1][0], x[1][1]);
                mma_bf(c1, a[3][0], a[3][1], a[3][2], a[3][3], x[1][2], x[1][3]);
                if (n < 3) {
                    asm volatile("" :: "r"(a[0][0]), "r"(a[1][0]), "r"(a[2][0]), "r"(a[3][0]) : "memory");
                    __syncwarp();
                    if (lane == 0) mbar_arrive(bar_free + 8 * n);
                }
                wa += PIECE; xa += 128;
            }
            if (warp == 0) TSTAMP(6);
            float h[2];
#pragma unroll
            for (int e = 0; e < 2; e++) {
                const float gv = rbf(c0[e] + c1[e]), uv = rbf(c0[2 + e] + c1[2 + e]);
                h[e] = rbf(gv * sigmoidf_(gv)) * uv;
            }
            uint32_t hp = pack_bf16(h[0], h[1]);
            asm volatile("movmatrix.sync.aligned.m8n8.trans.b16 %0, %0;" : "+r"(hp));
            sts32(sb + SF_H + (warp >> 1) * 256 + lane * 8 + (warp & 1) * 4, hp);
        }
    }
    bar_sync(9, NTHR);
    tag = tag_of(lds32(sb + SF_TK));
    float d[3][4];
    uint32_t off[3];
#pragma unroll
    for (int j = 0; j < 3; j++) {
        const int tile = 3 * warp + j, line = 9 * (8 * (mi >> 1) + r8) + (tile >> 2);
        off[j] = line * 128 + ((((2 * tile + (mi & 1)) ^ line) & 7) << 4);
        d[j][0] = d[j][1] = d[j][2] = d[j][3] = 0.f;
    }
#pragma unroll 1
    for (int i = 0; i < nunit / 2; i++) {
        const uint2 hv = lds64(sb + SF_H + i * 256 + lane * 8);
        const uint32_t base = i < 2 ? sb + SF_R + i * 18432 : sb + (i - 2) * PIECE;
        mbar_wait(bar_d + 8 * i);
        uint32_t a[3][4];
#pragma unroll
        for (int j = 0; j < 3; j++) ldsm4t(a[j], base + off[j]);
#pragma unroll
        for (int j = 0; j < 3; j++) mma_bf(d[j], a[j][0], a[j][1], a[j][2], a[j][3], hv.x, hv.y);
    }
    if (warp == 0) TSTAMP(7);
#pragma unroll
    for (int j = 0; j < 3; j++) {
        st_pkt(pdst + j * NFFN * 32, (__float_as_uint(d[j][0]) & ~3u) | tag, __float_as_uint(d[j][1]), __float_as_uint(d[j][2]), __float_as_uint(d[j][3]));
    }
    if (warp == 0) TSTAMP(8);
}

__global__ void __cluster_dims__(2, 1, 1) __launch_bounds__(NTHR, 1)
fused_kernel(const Params p, const __grid_constant__ CUtensorMap mU, const __grid_constant__ CUtensorMap mR, const __grid_constant__ CUtensorMap mG64,
             const __grid_constant__ CUtensorMap mU64, const __grid_constant__ CUtensorMap mG16, const __grid_constant__ CUtensorMap mU16,
             const __grid_constant__ CUtensorMap mWd) {
    extern __shared__ __align__(1024) uint8_t smem_raw[];
    const uint32_t sb = smem_u32(smem_raw);
    const uint32_t t0 = clk();
    const int bx = blockIdx.x;
    if (bx >= FFN0 && bx < FFN0 + NFFN) ffn_cta(p, &mR, &mG64, &mU64, &mG16, &mU16, &mWd, sb, bx - FFN0, t0);
    else {
        const int cb = bx < FFN0 ? bx : bx - NFFN;
        if (threadIdx.x < 256) { cluster_arrive_relaxed(); conv_warp(p, sb, cb); }
        else conv_helper(p, &mU, sb, cb, t0);
    }
}

typedef CUresult (*EncodeFn)(CUtensorMap*, CUtensorMapDataType, cuuint32_t, void*, const cuuint64_t*, const cuuint64_t*, const cuuint32_t*, const cuuint32_t*,
                             CUtensorMapInterleave, CUtensorMapSwizzle, CUtensorMapL2promotion, CUtensorMapFloatOOBfill);

CUtensorMap make_map(EncodeFn fn, const void* base, uint64_t inner, uint64_t outer, uint32_t bi, uint32_t bo, CUtensorMapSwizzle sw,
                     CUtensorMapL2promotion pr = CU_TENSOR_MAP_L2_PROMOTION_NONE) {
    CUtensorMap m;
    cuuint64_t dims[2] = {inner, outer};
    cuuint64_t strides[1] = {inner * 2};
    cuuint32_t box[2] = {bi, bo};
    cuuint32_t es[2] = {1, 1};
    fn(&m, CU_TENSOR_MAP_DATA_TYPE_BFLOAT16, 2, (void*)base, dims, strides, box, es, CU_TENSOR_MAP_INTERLEAVE_NONE, sw, pr, CU_TENSOR_MAP_FLOAT_OOB_FILL_NONE);
    return m;
}

}

extern "C" void kernel_launch(void* const* d_in, const int* in_sizes, int n_in, void* d_out, int out_size) {
    (void)in_sizes; (void)n_in; (void)out_size;
    static EncodeFn fn = nullptr;
    static Scratch* scr = nullptr;
    if (!fn) {
        void* ptr = nullptr; cudaDriverEntryPointQueryResult qr;
        cudaGetDriverEntryPoint("cuTensorMapEncodeTiled", &ptr, cudaEnableDefault, &qr);
        fn = (EncodeFn)ptr;
        cudaGetSymbolAddress((void**)&scr, g_scr);
        cudaFuncSetAttribute(fused_kernel, cudaFuncAttributeMaxDynamicSharedMemorySize, SMEM_BYTES);
    }
    typedef const __nv_bfloat16* bp;
    Params p;
    p.u = (bp)d_in[0]; p.Are = (bp)d_in[1]; p.Aim = (bp)d_in[2]; p.Bre = (bp)d_in[3]; p.Bim = (bp)d_in[4]; p.Cre = (bp)d_in[5]; p.Cim = (bp)d_in[6];
    p.logdt = (bp)d_in[7]; p.Dskip = (bp)d_in[8]; p.wr = (bp)d_in[10]; p.gatew = (bp)d_in[14];
    p.out = (__nv_bfloat16*)d_out; p.scr = scr;
    CUtensorMap mU;
    {
        cuuint64_t dims[4] = {DM, 2, L_SEQ / 16, 8};
        cuuint64_t strides[3] = {DM * 2, 16 * DM * 2, 2 * DM * 2};
        cuuint32_t box[4] = {16, 2, 16, 8};
        cuuint32_t es[4] = {1, 1, 1, 1};
        fn(&mU, CU_TENSOR_MAP_DATA_TYPE_BFLOAT16, 4, d_in[0], dims, strides, box, es, CU_TENSOR_MAP_INTERLEAVE_NONE, CU_TENSOR_MAP_SWIZZLE_32B,
           CU_TENSOR_MAP_L2_PROMOTION_NONE, CU_TENSOR_MAP_FLOAT_OOB_FILL_NONE);
    }
    const CUtensorMap mR = make_map(fn, d_in[0], 64, L_SEQ * 9, 64, 72, CU_TENSOR_MAP_SWIZZLE_128B);
    const CUtensorMap mG64 = make_map(fn, d_in[11], FF, DM, 64, 64, CU_TENSOR_MAP_SWIZZLE_128B);
    const CUtensorMap mU64 = make_map(fn, d_in[12], FF, DM, 64, 64, CU_TENSOR_MAP_SWIZZLE_128B);
    const CUtensorMap mG16 = make_map(fn, d_in[11], FF, DM, 16, 64, CU_TENSOR_MAP_SWIZZLE_32B, CU_TENSOR_MAP_L2_PROMOTION_L2_128B);
    const CUtensorMap mU16 = make_map(fn, d_in[12], FF, DM, 16, 64, CU_TENSOR_MAP_SWIZZLE_32B, CU_TENSOR_MAP_L2_PROMOTION_L2_128B);
    const CUtensorMap mWd = make_map(fn, d_in[13], 64, FF * 9, 64, 144, CU_TENSOR_MAP_SWIZZLE_128B);
    fused_kernel<<<NCTA, NTHR, SMEM_BYTES>>>(p, mU, mR, mG64, mU64, mG16, mU16, mWd);
}
```

```cpp
#include <cuda_runtime.h>
#include <cuda_bf16.h>
#include <cuda_fp16.h>
#include <cuda.h>
#include <stdint.h>

#define RDELAY 1000
#define UDELAY 600
#define WDELAY 1800
#define PDELAY 900
#define KDELAY 6400
#define SPIN
#define FDELAY 600
#define DUPA a[j1][0] + oz
#define WWIN 3

namespace {

constexpr int L_SEQ = 2048, DM = 576, NST = 128, FF = 4608;
constexpr int NCTA = 132, NFFN = 60, FFN0 = 8, NTHR = 512;

struct Scratch {
    unsigned launch; unsigned pad0[31];
    uint32_t sel[32];
    uint32_t rec[L_SEQ];
    uint4 kx[288 * 3 * 32];
    uint4 part[36 * NFFN * 32];
};
__device__ Scratch g_scr;

struct Params {
    const __nv_bfloat16 *Are, *Aim, *Bre, *Bim, *Cre, *Cim, *logdt, *Dskip, *u, *wr, *gatew;
    __nv_bfloat16* out;
    Scratch* scr;
};

#define TSTAMP(i)

__device__ __forceinline__ uint32_t smem_u32(const void* p) { return (uint32_t)__cvta_generic_to_shared(p); }
__device__ __forceinline__ uint32_t pack_bf16(float lo, float hi) { uint32_t r; asm("cvt.rn.bf16x2.f32 %0, %1, %2;" : "=r"(r) : "f"(hi), "f"(lo)); return r; }
__device__ __forceinline__ uint32_t pack_f16(float lo, float hi) { uint32_t r; asm("cvt.rn.f16x2.f32 %0, %1, %2;" : "=r"(r) : "f"(hi), "f"(lo)); return r; }
__device__ __forceinline__ float bf_lo(uint32_t w) { return __uint_as_float(w << 16); }
__device__ __forceinline__ float bf_hi(uint32_t w) { return __uint_as_float(w & 0xffff0000u); }
__device__ __forceinline__ uint32_t cvt_bf16(float x) { uint32_t r; asm volatile("cvt.rn.bf16x2.f32 %0, %1, %1;" : "=r"(r) : "f"(x)); return r; }
__device__ __forceinline__ float rbf(float x) { return bf_lo(pack_bf16(x, 0.f)); }
__device__ __forceinline__ uint32_t hmul2(uint32_t a, uint32_t b) { __nv_bfloat162 r = __hmul2_rn(*(__nv_bfloat162*)&a, *(__nv_bfloat162*)&b); return *(uint32_t*)&r; }
__device__ __forceinline__ uint32_t hadd2(uint32_t a, uint32_t b) { __nv_bfloat162 r = __hadd2_rn(*(__nv_bfloat162*)&a, *(__nv_bfloat162*)&b); return *(uint32_t*)&r; }
__device__ __forceinline__ uint32_t hfma2(uint32_t a, uint32_t b, uint32_t c) { uint32_t r; asm("fma.rn.bf16x2 %0, %1, %2, %3;" : "=r"(r) : "r"(a), "r"(b), "r"(c)); return r; }
__device__ __forceinline__ uint32_t hsub2(uint32_t a, uint32_t b) { __nv_bfloat162 r = __hsub2_rn(*(__nv_bfloat162*)&a, *(__nv_bfloat162*)&b); return *(uint32_t*)&r; }
__device__ __forceinline__ void mma_bf(float (&c)[4], uint32_t a0, uint32_t a1, uint32_t a2, uint32_t a3, uint32_t b0, uint32_t b1) {
    asm("mma.sync.aligned.m16n8k16.row.col.f32.bf16.bf16.f32 {%0,%1,%2,%3}, {%4,%5,%6,%7}, {%8,%9}, {%0,%1,%2,%3};"
        : "+f"(c[0]), "+f"(c[1]), "+f"(c[2]), "+f"(c[3]) : "r"(a0), "r"(a1), "r"(a2), "r"(a3), "r"(b0), "r"(b1));
}
__device__ __forceinline__ void mma_bf0(float (&c)[4], uint32_t a0, uint32_t a1, uint32_t a2, uint32_t a3, uint32_t b0, uint32_t b1) {
    asm("mma.sync.aligned.m16n8k16.row.col.f32.bf16.bf16.f32 {%0,%1,%2,%3}, {%4,%5,%6,%7}, {%8,%9}, {%10,%10,%10,%10};"
        : "=f"(c[0]), "=f"(c[1]), "=f"(c[2]), "=f"(c[3]) : "r"(a0), "r"(a1), "r"(a2), "r"(a3), "r"(b0), "r"(b1), "f"(0.f));
}
__device__ __forceinline__ void mma_bf8(float (&c)[4], uint32_t a0, uint32_t a1, uint32_t b0) {
    asm("mma.sync.aligned.m16n8k8.row.col.f32.bf16.bf16.f32 {%0,%1,%2,%3}, {%4,%5}, {%6}, {%0,%1,%2,%3};"
        : "+f"(c[0]), "+f"(c[1]), "+f"(c[2]), "+f"(c[3]) : "r"(a0), "r"(a1), "r"(b0));
}
__device__ __forceinline__ void mma_f16(float (&c)[4], uint32_t a0, uint32_t a1, uint32_t a2, uint32_t a3, uint32_t b0, uint32_t b1) {
    asm("mma.sync.aligned.m16n8k16.row.col.f32.f16.f16.f32 {%0,%1,%2,%3}, {%4,%5,%6,%7}, {%8,%9}, {%0,%1,%2,%3};"
        : "+f"(c[0]), "+f"(c[1]), "+f"(c[2]), "+f"(c[3]) : "r"(a0), "r"(a1), "r"(a2), "r"(a3), "r"(b0), "r"(b1));
}
__device__ __forceinline__ uint32_t lds16(uint32_t a) { uint32_t v; asm volatile("ld.shared.u16 %0, [%1];" : "=r"(v) : "r"(a)); return v; }
__device__ __forceinline__ uint32_t lds8(uint32_t a) { uint32_t v; asm volatile("ld.shared.u8 %0, [%1];" : "=r"(v) : "r"(a)); return v; }
__device__ __forceinline__ uint32_t lds32(uint32_t a) { uint32_t v; asm volatile("ld.shared.u32 %0, [%1];" : "=r"(v) : "r"(a)); return v; }
__device__ __forceinline__ uint32_t lds32v(uint32_t a) { uint32_t v; asm volatile("ld.volatile.shared.u32 %0, [%1];" : "=r"(v) : "r"(a)); return v; }
__device__ __forceinline__ uint2 lds64(uint32_t a) { uint2 v; asm volatile("ld.shared.v2.u32 {%0,%1}, [%2];" : "=r"(v.x), "=r"(v.y) : "r"(a)); return v; }
__device__ __forceinline__ uint4 lds128(uint32_t a) { uint4 v; asm volatile("ld.shared.v4.u32 {%0,%1,%2,%3}, [%4];" : "=r"(v.x), "=r"(v.y), "=r"(v.z), "=r"(v.w) : "r"(a)); return v; }
__device__ __forceinline__ void ldsm4(uint32_t (&r)[4], uint32_t a) {
    asm volatile("ldmatrix.sync.aligned.m8n8.x4.shared.b16 {%0,%1,%2,%3}, [%4];" : "=r"(r[0]), "=r"(r[1]), "=r"(r[2]), "=r"(r[3]) : "r"(a));
}
__device__ __forceinline__ void ldsm4t(uint32_t (&r)[4], uint32_t a) {
    asm volatile("ldmatrix.sync.aligned.m8n8.x4.trans.shared.b16 {%0,%1,%2,%3}, [%4];" : "=r"(r[0]), "=r"(r[1]), "=r"(r[2]), "=r"(r[3]) : "r"(a));
}
__device__ __forceinline__ void sts16(uint32_t a, uint32_t v) { asm volatile("st.shared.u16 [%0], %1;" :: "r"(a), "r"(v) : "memory"); }
__device__ __forceinline__ void sts32(uint32_t a, uint32_t v) { asm volatile("st.shared.u32 [%0], %1;" :: "r"(a), "r"(v) : "memory"); }
__device__ __forceinline__ void sts64(uint32_t a, uint32_t x, uint32_t y) { asm volatile("st.shared.v2.u32 [%0], {%1,%2};" :: "r"(a), "r"(x), "r"(y) : "memory"); }
__device__ __forceinline__ void sts128(uint32_t a, uint32_t x, uint32_t y, uint32_t z, uint32_t w) {
    asm volatile("st.shared.v4.u32 [%0], {%1,%2,%3,%4};" :: "r"(a), "r"(x), "r"(y), "r"(z), "r"(w) : "memory");
}
__device__ __forceinline__ void stsm2(uint32_t a, uint32_t x, uint32_t y) {
    asm volatile("stmatrix.sync.aligned.m8n8.x2.shared.b16 [%0], {%1,%2};" :: "r"(a), "r"(x), "r"(y) : "memory");
}
__device__ __forceinline__ void stsm4t(uint32_t a, uint32_t r0, uint32_t r1, uint32_t r2, uint32_t r3) {
    asm volatile("stmatrix.sync.aligned.m8n8.x4.trans.shared.b16 [%0], {%1,%2,%3,%4};" :: "r"(a), "r"(r0), "r"(r1), "r"(r2), "r"(r3) : "memory");
}
__device__ __forceinline__ void st_async64(uint32_t a, uint32_t x, uint32_t y, uint32_t bar) {
    asm volatile("st.async.weak.shared::cluster.mbarrier::complete_tx::bytes.v2.b32 [%0], {%1,%2}, [%3];" :: "r"(a), "r"(x), "r"(y), "r"(bar) : "memory");
}
__device__ __forceinline__ void st_async128(uint32_t a, uint32_t x, uint32_t y, uint32_t z, uint32_t w, uint32_t bar) {
    asm volatile("st.async.weak.shared::cluster.mbarrier::complete_tx::bytes.v4.b32 [%0], {%1,%2,%3,%4}, [%5];" :: "r"(a), "r"(x), "r"(y), "r"(z), "r"(w), "r"(bar) : "memory");
}
__device__ __forceinline__ void mbar_init(uint32_t b, uint32_t cnt) { asm volatile("mbarrier.init.shared::cta.b64 [%0], %1;" :: "r"(b), "r"(cnt) : "memory"); }
__device__ __forceinline__ void mbar_fence_init() { asm volatile("fence.mbarrier_init.release.cluster;" ::: "memory"); }
__device__ __forceinline__ void mbar_expect(uint32_t b, uint32_t bytes) { asm volatile("mbarrier.arrive.expect_tx.shared::cta.b64 _, [%0], %1;" :: "r"(b), "r"(bytes) : "memory"); }
__device__ __forceinline__ void mbar_arrive(uint32_t b) { asm volatile("mbarrier.arrive.shared::cta.b64 _, [%0];" :: "r"(b) : "memory"); }
__device__ __forceinline__ void mbar_wait(uint32_t b) {
    asm volatile("{ .reg .pred p; .reg .u32 n; mov.u32 n, 0;\n"
                 "W: mbarrier.try_wait.parity.shared::cta.b64 p, [%0], 0; @p bra D; add.u32 n, n, 1; setp.lt.u32 p, n, 4000000; @p bra W; trap;\n"
                 "D: }" :: "r"(b) : "memory");
}
__device__ __forceinline__ bool mbar_test(uint32_t b) {
    uint32_t d; asm volatile("{ .reg .pred p; mbarrier.test_wait.parity.shared::cta.b64 p, [%1], 0; selp.u32 %0, 1, 0, p; }" : "=r"(d) : "r"(b) : "memory"); return d;
}
__device__ __forceinline__ void tma2d(uint32_t dst, const CUtensorMap* m, int c0, int c1, uint32_t bar) {
    asm volatile("cp.async.bulk.tensor.2d.shared::cluster.global.mbarrier::complete_tx::bytes [%0], [%1, {%3, %4}], [%2];"
                 :: "r"(dst), "l"(m), "r"(bar), "r"(c0), "r"(c1) : "memory");
}
__device__ __forceinline__ void tma5d(uint32_t dst, const CUtensorMap* m, int c0, int c1, int c2, int c3, int c4, uint32_t bar) {
    asm volatile("cp.async.bulk.tensor.5d.shared::cluster.global.mbarrier::complete_tx::bytes [%0], [%1, {%3, %4, %5, %6, %7}], [%2];"
                 :: "r"(dst), "l"(m), "r"(bar), "r"(c0), "r"(c1), "r"(c2), "r"(c3), "r"(c4) : "memory");
}
__device__ __forceinline__ uint32_t mapa(uint32_t a, uint32_t rank) { uint32_t r; asm("mapa.shared::cluster.u32 %0, %1, %2;" : "=r"(r) : "r"(a), "r"(rank)); return r; }
__device__ __forceinline__ void prefetch_map(const CUtensorMap* m) { asm volatile("prefetch.tensormap [%0];" :: "l"(m) : "memory"); }
__device__ __forceinline__ void bar_sync(int id, int n) { asm volatile("bar.sync %0, %1;" :: "r"(id), "r"(n) : "memory"); }
__device__ __forceinline__ void bar_arrive(int id, int n) { asm volatile("bar.arrive %0, %1;" :: "r"(id), "r"(n) : "memory"); }
__device__ __forceinline__ void cluster_arrive_relaxed() { asm volatile("barrier.cluster.arrive.relaxed.aligned;" ::: "memory"); }
__device__ __forceinline__ void cluster_wait() { asm volatile("barrier.cluster.wait.aligned;" ::: "memory"); }
__device__ __forceinline__ uint32_t ld_rlx32(const void* p) { uint32_t v; asm volatile("ld.relaxed.gpu.global.u32 %0, [%1];" : "=r"(v) : "l"(p) : "memory"); return v; }
__device__ __forceinline__ uint4 ld_rlx128(const void* p) {
    uint4 v; asm volatile("ld.relaxed.gpu.global.v4.u32 {%0,%1,%2,%3}, [%4];" : "=r"(v.x), "=r"(v.y), "=r"(v.z), "=r"(v.w) : "l"(p) : "memory"); return v;
}
__device__ __forceinline__ uint32_t take_ticket(unsigned* p) { uint32_t v; asm volatile("atom.relaxed.gpu.global.add.u32 %0, [%1], 1;" : "=r"(v) : "l"(p) : "memory"); return v; }
__device__ __forceinline__ void st_rlx32(void* p, uint32_t v) { asm volatile("st.relaxed.gpu.global.u32 [%0], %1;" :: "l"(p), "r"(v) : "memory"); }
__device__ __forceinline__ void st_pkt(void* p, uint32_t x, uint32_t y, uint32_t z, uint32_t w) {
    asm volatile("{ .reg .b64 lo, hi; .reg .b128 v; mov.b64 lo, {%1, %2}; mov.b64 hi, {%3, %4}; mov.b128 v, {lo, hi}; st.relaxed.gpu.global.b128 [%0], v; }"
                 :: "l"(p), "r"(x), "r"(y), "r"(z), "r"(w) : "memory");
}
__device__ __forceinline__ uint4 ld_pkt(const void* p) {
    uint4 r;
    asm volatile("{ .reg .b64 lo, hi; .reg .b128 v; ld.relaxed.gpu.global.b128 v, [%4]; mov.b128 {lo, hi}, v; mov.b64 {%0, %1}, lo; mov.b64 {%2, %3}, hi; }"
                 : "=r"(r.x), "=r"(r.y), "=r"(r.z), "=r"(r.w) : "l"(p) : "memory");
    return r;
}
__device__ __forceinline__ uint32_t tag_of(uint32_t ticket) { return ticket / NCTA % 3u + 1u; }
__device__ __forceinline__ uint2 ldg64(const void* p) { uint2 v; asm volatile("ld.global.nc.v2.u32 {%0,%1}, [%2];" : "=r"(v.x), "=r"(v.y) : "l"(p)); return v; }
__device__ __forceinline__ uint4 ldg128(const void* p) { uint4 v; asm volatile("ld.global.nc.v4.u32 {%0,%1,%2,%3}, [%4];" : "=r"(v.x), "=r"(v.y), "=r"(v.z), "=r"(v.w) : "l"(p)); return v; }
__device__ __forceinline__ uint32_t ldg32(const void* p) { uint32_t v; asm volatile("ld.global.nc.u32 %0, [%1];" : "=r"(v) : "l"(p)); return v; }
__device__ __forceinline__ uint32_t ldg16(const void* p) { uint32_t v; asm volatile("ld.global.nc.u16 %0, [%1];" : "=r"(v) : "l"(p)); return v; }
__device__ __forceinline__ int warp_id() { return __shfl_sync(0xffffffffu, threadIdx.x >> 5, 0); }
__device__ __forceinline__ uint32_t clk() { uint32_t t; asm volatile("mov.u32 %0, %clock;" : "=r"(t) :: "memory"); return t; }
__device__ __forceinline__ void spin_until(uint32_t t0, uint32_t d) { while (clk() - t0 < d) { SPIN; } }
__device__ __forceinline__ float sigmoidf_(float x) { return __fdividef(1.0f, 1.0f + __expf(-x)); }
__device__ __forceinline__ int key_row(uint32_t key) { return 2047 - (int)(key & 2047u); }
__device__ __forceinline__ float key_val(uint32_t key) {
    const uint32_t o = key & 0xffff0000u; return __uint_as_float((o & 0x80000000u) ? (o & 0x7fffffffu) : (~o & 0xffff0000u));
}
#define POLL_GUARD(it) if (++(it) > (1 << 20)) __trap()

constexpr int UT_PL = 2240, UT_STRIDE = 4544;
constexpr int KT_P = 0, KT_P4 = 544 * 4, KT_P8 = KT_P4 + 184 * 4, KT_BYTES = KT_P8 + 144 * 4;
constexpr int KG_ROW = 272, KG_STAGE = 33 * KG_ROW;
constexpr int OUT_HALF = 2368, OUT_STAGE = 2 * OUT_HALF;
constexpr int SC_UTILE = 0;
constexpr int SC_UT = 32768;
constexpr int SC_STG = SC_UT + 8 * UT_STRIDE;
constexpr int SC_KT = SC_STG + 8 * KG_STAGE;
constexpr int SC_OUT = SC_KT + 8 * KT_BYTES;
constexpr int SC_RED = SC_OUT + 8 * OUT_STAGE;
constexpr int SC_BAR = SC_RED + 2048;
constexpr int SC_END = SC_BAR + 256;
static_assert(SC_STG % 128 == 0 && SC_OUT % 128 == 0 && SC_KT % 16 == 0, "align");
constexpr int PIECE = 20480;
constexpr int SF_R = 9 * PIECE;
constexpr int SF_XS = SF_R + 36864;
constexpr int SF_STG = 4 * PIECE, SF_R4 = 8 * PIECE + 8192;
constexpr int SF_LIST = SF_XS, SF_WR = SF_XS + 4096;
constexpr int SF_H = SF_XS + 9344;
constexpr int SF_BAR = SF_H + 1280;
constexpr int SF_MAX = SF_BAR + 208, SF_CNT = SF_MAX + 64, SF_TK = SF_CNT + 4, SF_CLK = SF_CNT + 8, SF_SEL = SF_CNT + 16;
constexpr int SF_END = SF_SEL + 32;
constexpr int SM_TIM = SF_END;
constexpr int SMEM_BYTES = SF_END + 256;
static_assert(SF_STG + 10 * KG_STAGE <= SF_R4 && SMEM_BYTES <= 232448 && SC_END <= SF_END, "smem");

struct cplx { float re, im; };
struct h2c { uint32_t re, im; };
__device__ __forceinline__ cplx csq(cplx a) {
    cplx r; r.re = a.re * a.re - a.im * a.im;
    asm("{ .reg .f32 t; mul.f32 t, %1, %2; mul.f32 %0, t, 0f40000000; }" : "=f"(r.im) : "f"(a.re), "f"(a.im));
    return r;
}
__device__ __forceinline__ float ex2(float x) { float m; asm("ex2.approx.ftz.f32 %0, %1;" : "=f"(m) : "f"(x)); return m; }
__device__ __forceinline__ cplx cexp2(float x, float y) {
    const float m = ex2(x);
    cplx o; o.re = m * __cosf(y); o.im = m * __sinf(y); return o;
}
__device__ __forceinline__ h2c hpack(cplx a, cplx b) { h2c r; r.re = pack_f16(a.re, b.re); r.im = pack_f16(a.im, b.im); return r; }
__device__ __forceinline__ h2c hmulc(h2c a, h2c m) {
    h2c r;
    asm("{ .reg .b32 s, t; mul.f16x2 s, %3, %5; mul.f16x2 t, %3, %4; neg.f16x2 s, s; fma.rn.f16x2 %0, %2, %4, s; fma.rn.f16x2 %1, %2, %5, t; }"
        : "=&r"(r.re), "=r"(r.im) : "r"(a.re), "r"(a.im), "r"(m.re), "r"(m.im));
    return r;
}
__device__ __forceinline__ h2c hmulj(h2c a, h2c m) {
    h2c r;
    asm("{ .reg .b32 s, t; mul.f16x2 s, %3, %5; mul.f16x2 t, %2, %5; neg.f16x2 t, t; fma.rn.f16x2 %0, %2, %4, s; fma.rn.f16x2 %1, %3, %4, t; }"
        : "=&r"(r.re), "=r"(r.im) : "r"(a.re), "r"(a.im), "r"(m.re), "r"(m.im));
    return r;
}

struct KParams { uint32_t v[6], logdt, dskip; };
__device__ __forceinline__ KParams kload(const Params& p, int ch, int half) {
    KParams k;
    const int o = ch * NST + 64 * half + 2 * (threadIdx.x & 31);
    const __nv_bfloat16* a[8] = {p.Are + o, p.Aim + o, p.Bre + o, p.Bim + o, p.Cre + o, p.Cim + o, p.logdt + ch, p.Dskip + ch};
#pragma unroll
    for (int i = 0; i < 6; i++) k.v[i] = ldg32(a[i]);
    k.logdt = ldg16(a[6]); k.dskip = ldg16(a[7]);
    return k;
}

__device__ __forceinline__ void kgen(const KParams& k, uint32_t stage, float (&kv)[21], float& fin, uint32_t sb) {
    const int lane = threadIdx.x & 31, mi = lane >> 3, r8 = lane & 7;
    const uint32_t (&v)[6] = k.v;
    const uint32_t w2 = stage + (lane & 15) * 16, w1 = stage + lane * 4;
    auto put = [&](int row, h2c x) { stsm2(w2 + row * KG_ROW, x.re, x.im); };
    auto keep = [&](int row, h2c x) { sts32(w1 + row * KG_ROW, x.re); sts32(w1 + row * KG_ROW + 128, x.im); };
    sts32(w1, 0x3c003c00u); sts32(w1 + 128, 0u);
    const float dt = rbf(ex2(bf_lo(k.logdt) * 1.4426950408889634f));
    const float dl = dt * 1.4426950408889634f;
    const float xa = bf_lo(v[0]) * dl, xb = bf_hi(v[0]) * dl, ya = bf_lo(v[1]) * dt, yb = bf_hi(v[1]) * dt;
    cplx a = cexp2(xa, ya), b = cexp2(xb, yb), c = cexp2(64.f * xa, 64.f * ya), d = cexp2(64.f * xb, 64.f * yb);
    cplx Wa, Wb;
    Wa.re = bf_lo(v[4]) * bf_lo(v[2]) - bf_lo(v[5]) * bf_lo(v[3]); Wa.im = bf_lo(v[4]) * bf_lo(v[3]) + bf_lo(v[5]) * bf_lo(v[2]);
    Wb.re = bf_hi(v[4]) * bf_hi(v[2]) - bf_hi(v[5]) * bf_hi(v[3]); Wb.im = bf_hi(v[4]) * bf_hi(v[3]) + bf_hi(v[5]) * bf_hi(v[2]);
    const float mx = fmaxf(fmaxf(fabsf(Wa.re), fabsf(Wa.im)), fmaxf(fabsf(Wb.re), fabsf(Wb.im)));
    const uint32_t ex = max(__reduce_max_sync(0xffffffffu, __float_as_uint(mx)) >> 23, 10u);
    const float sc = __uint_as_float((263u - ex) << 23);
    fin = dt * __uint_as_float((ex - 9u) << 23);
    Wa.re *= sc; Wa.im *= sc; Wb.re *= sc; Wb.im *= sc;
    kv[20] = (float)__reduce_add_sync(0xffffffffu, __float2int_rn((Wa.re + Wb.re) * 32768.f)) * (1.f / 32768.f);
    h2c c1;
    {
        cplx p, q;
        p.re = Wa.re * a.re - Wa.im * a.im; p.im = -(Wa.re * a.im) - Wa.im * a.re; q.re = Wb.re * b.re - Wb.im * b.im; q.im = -(Wb.re * b.im) - Wb.im * b.re;
        c1 = hpack(p, q);
    }
    const h2c z1 = hpack(a, b); a = csq(a); b = csq(b);
    const h2c z64 = hpack(c, d); c = csq(c); d = csq(d);
    const h2c z2 = hpack(a, b); a = csq(a); b = csq(b);
    const h2c z128 = hpack(c, d); c = csq(c); d = csq(d);
    const h2c z4 = hpack(a, b); a = csq(a); b = csq(b);
    const h2c z256 = hpack(c, d); c = csq(c); d = csq(d);
    const h2c z8 = hpack(a, b); a = csq(a); b = csq(b);
    const h2c z512 = hpack(c, d);
    const h2c z16 = hpack(a, b); a = csq(a); b = csq(b);
    const h2c z32 = hpack(a, b);
    keep(32, z64);
    const h2c c2 = hmulj(c1, z1), c3 = hmulj(c1, z2), c4 = hmulj(c2, z2), c6 = hmulj(c2, z4), c8 = hmulj(c4, z4);
    keep(8, c1); keep(9, c2); keep(10, c3); keep(11, c4); put(12, hmulj(c1, z4)); keep(13, c6); put(14, hmulj(c3, z4)); keep(15, c8);
    const h2c e260 = hmulj(c4, z256), e264 = hmulj(c8, z256), e776 = hmulj(e264, z512), e840 = hmulj(e776, z64);
    put(16, hmulj(c2, z256)); put(17, hmulj(c4, z512)); keep(18, e260); put(19, hmulj(c8, z512)); put(20, hmulj(c6, z256)); put(21, hmulj(e260, z512)); keep(22, e264); keep(23, e776);
    const h2c z24 = hmulc(z8, z16);
    keep(1, z8); keep(2, z16); keep(3, z24); keep(4, z32); put(5, hmulc(z8, z32)); put(6, hmulc(z16, z32)); put(7, hmulc(z24, z32));
    const h2c d0 = hmulj(e840, z128), d1 = hmulj(e840, z256), d3 = hmulj(e840, z512), d2 = hmulj(d0, z256);
    keep(24, d0); keep(26, d1); keep(30, d3); keep(28, d2); put(25, hmulj(d0, z512)); put(27, hmulj(d1, z512)); put(31, hmulj(d3, z512)); put(29, hmulj(d2, z512));
    __syncwarp();
    if (threadIdx.x < 32) TSTAMP(25); if (threadIdx.x >> 5 == 2) TSTAMP(28);
    const uint32_t ra = stage + ((mi & 1) ? 32 : r8) * KG_ROW + (mi >> 1) * 128, rb = stage + (8 + r8) * KG_ROW + (mi & 1) * 128 + (mi >> 1) * 16;
    float acc[5][4];
#pragma unroll
    for (int i = 0; i < 5; i++) acc[i][0] = acc[i][1] = acc[i][2] = acc[i][3] = 0.f;
#pragma unroll
    for (int s = 0; s < 4; s++) {
        uint32_t A[2][4], B[3][4];
        ldsm4(A[0], ra + 32 * s); ldsm4(A[1], ra + 32 * s + 16);
        ldsm4(B[0], rb + 32 * s); ldsm4(B[1], rb + 32 * s + 8 * KG_ROW); ldsm4(B[2], rb + 32 * s + 16 * KG_ROW);
#pragma unroll
        for (int e = 0; e < 2; e++) {
            const h2c p0 = {A[e][0], A[e][2]}, m = {A[e][1], A[e][3]};
            const h2c p1 = hmulc(p0, m), p2 = hmulc(p1, m), p3 = hmulc(p2, m);
            mma_f16(acc[1], p1.re, p2.re, p1.im, p2.im, B[0][2 * e], B[0][2 * e + 1]);
            mma_f16(acc[3], p1.re, p2.re, p1.im, p2.im, B[1][2 * e], B[1][2 * e + 1]);
            mma_f16(acc[4], p1.re, p2.re, p1.im, p2.im, B[2][2 * e], B[2][2 * e + 1]);
            mma_f16(acc[0], p0.re, p3.re, p0.im, p3.im, B[0][2 * e], B[0][2 * e + 1]);
            mma_f16(acc[2], p0.re, p3.re, p0.im, p3.im, B[1][2 * e], B[1][2 * e + 1]);
        }
    }
#pragma unroll
    for (int q = 0; q < 4; q++) {
        const int i = (q == 1 || q == 2), h = 2 * (q >> 1);
        kv[2 * q] = acc[i][h]; kv[2 * q + 1] = acc[i][h + 1]; kv[8 + q] = acc[2 + i][h]; kv[12 + q] = acc[2 + i][h + 1]; kv[16 + q] = acc[4][q];
    }
}
__device__ __forceinline__ void ksend(const float (&kv)[21], float fin, uint32_t stage, int bar) {
    const uint32_t a = stage + (threadIdx.x & 31) * 16;
    __syncwarp();
#pragma unroll
    for (int i = 0; i < 5; i++) sts128(a + 512 * i, __float_as_uint(kv[4 * i] * fin), __float_as_uint(kv[4 * i + 1] * fin), __float_as_uint(kv[4 * i + 2] * fin), __float_as_uint(kv[4 * i + 3] * fin));
    sts32(stage + 2560, __float_as_uint(kv[20] * fin));
    bar_arrive(bar, 64);
}
__device__ __forceinline__ void krecv(float (&kv)[21], float fin, uint32_t stage, int bar, uint32_t dskip) {
    const uint32_t a = stage + (threadIdx.x & 31) * 16;
    bar_sync(bar, 64);
#pragma unroll
    for (int i = 0; i < 5; i++) {
        const uint4 x = lds128(a + 512 * i);
        kv[4 * i] = kv[4 * i] * fin + __uint_as_float(x.x); kv[4 * i + 1] = kv[4 * i + 1] * fin + __uint_as_float(x.y);
        kv[4 * i + 2] = kv[4 * i + 2] * fin + __uint_as_float(x.z); kv[4 * i + 3] = kv[4 * i + 3] * fin + __uint_as_float(x.w);
    }
    kv[20] = kv[20] * fin + __uint_as_float(lds32(stage + 2560)) + bf_lo(dskip);
}

__device__ __forceinline__ void ktables(float (&kv)[21], uint32_t kt) {
    const int lane = threadIdx.x & 31, g = lane >> 2, t = lane & 3;
    const uint32_t h512 = cvt_bf16(__shfl_sync(0xffffffffu, kv[11], 31));
    if (lane >= 30) kv[11] = lane == 31 ? 0.f : kv[11] - bf_lo(h512);
    float carry = kv[20];
    if (lane == 0) { sts16(kt + KT_P + 15 * 4, cvt_bf16(carry)); sts16(kt + KT_P4 + 24 * 4, h512); sts16(kt + KT_P4 + 28 * 4 + 2, h512); }
#pragma unroll
    for (int q = 0; q < 8; q++) {
        const float hi = q < 4 ? kv[2 * q + 1] : kv[4 + q];
        const float sh = __shfl_sync(0xffffffffu, hi, (lane + 31) & 31);
        const float prev = lane ? sh : carry;
        carry = sh;
        const float lo = q < 4 ? kv[2 * q] : ((lane & 1) ? hi : prev);
        sts64(kt + KT_P + (64 * q + 16) * 4 + lane * 8, pack_bf16(lo, prev), pack_bf16(hi, lo));
    }
    const uint32_t a4 = kt + KT_P4 + (25 + 2 * g + (t & 1) + 64 * (t >> 1)) * 4, a8 = kt + KT_P8 + (12 + 16 * t + g) * 4;
#pragma unroll
    for (int q = 0; q < 4; q++) {
        const uint32_t x = cvt_bf16(kv[12 + q]), y = cvt_bf16(kv[16 + q]);
        sts16(a4 + 64 * q, x); sts16(a4 + 64 * q + 18, x);
        sts16(a8 + 256 * (q & 1) + 32 * (q >> 1), y); sts16(a8 + 256 * (q & 1) + 32 * (q >> 1) + 10, y);
    }
    __syncwarp();
}

__device__ __forceinline__ uint32_t band(int e, int c, int h) {
    return (((unsigned)(e - c + h) <= 2u * h) ? 0x3f80u : 0u) | (((unsigned)(e + 1 - c + h) <= 2u * h) ? 0x3f800000u : 0u);
}

__device__ __forceinline__ void conv_warp(uint32_t sb, int rank) {
    const int warp = warp_id(), lane = threadIdx.x & 31, g = lane >> 2, t = lane & 3, mi = lane >> 3, r8 = lane & 7;
    const uint32_t kt = sb + SC_KT + warp * KT_BYTES, ut = sb + SC_UT + warp * UT_STRIDE + 128;
    float acc[16][4];
    const int d0 = g - 2 * t;
    const uint32_t oz = blockIdx.y;
    {
        uint32_t kb[8][2];
#pragma unroll
        for (int l = 0; l < 8; l++) { const uint2 x = lds64(kt + KT_P8 + (6 + 8 * l + d0) * 8); kb[l][0] = x.x; kb[l][1] = x.y; }
        const uint32_t w0 = band(4 * t, 4 + g, 4), w1 = band(4 * t, 4 + g, 3), w2 = band(4 * t + 2, 4 + g, 4), w3 = band(4 * t + 2, 4 + g, 3);
        const uint32_t a0 = ut + g * 16 + (t == 0 ? UT_PL - 8 : t == 3 ? UT_PL : 8 * (t - 1));
        const uint32_t a1 = ut + g * 16 + (t == 0 ? -8 : t == 3 ? 0 : UT_PL - 16 + 8 * (t - 1));
        mbar_wait(sb + SC_BAR + 32);
        if (warp == 0) TSTAMP(2);
#pragma unroll
        for (int j = 0; j < 8; j++) {
            const uint2 x = lds64(a0 + 128 * j - 16), y = lds64(a1 + 128 * j), z = lds64(a0 + 128 * j);
            float X[4], Y[4], Z[4];
            mma_bf0(X, w0, w1, w2, w3, x.x, x.y); mma_bf0(Y, w0, w1, w2, w3, y.x, y.y); mma_bf0(Z, w0, w1, w2, w3, z.x, z.y);
            const uint32_t q0 = pack_bf16(Y[2], Y[3]), q1 = pack_bf16(Z[2], Z[3]), q2 = pack_bf16(X[0], X[1]), q3 = pack_bf16(Y[0], Y[1]);
#pragma unroll
            for (int l = 0; l < 8 - j; l++) {
                if (j == 0) mma_bf0(acc[8 + l], q0, q1, q2, q3, kb[l][0], kb[l][1]);
                else mma_bf(acc[8 + j + l], q0, q1, q2, q3, kb[l][0], kb[l][1]);
            }
        }
    }
    TSTAMP(40 + warp);
    const uint32_t ub = ut + (mi & 1) * UT_PL + (mi >> 1) * 128 + r8 * 16;
    const uint32_t kp = kt + KT_P + (15 + d0) * 4;
    {
        uint32_t a[4][4], b[8][4];
        uint32_t k1 = kp, u1 = ub;
        auto lda = [&](int j1) { a[j1][0] = lds32(k1 + 512 * j1); a[j1][1] = lds32(k1 + 512 * j1 + 32); a[j1][2] = lds32(k1 + 512 * j1 - 32); a[j1][3] = DUPA; };
        lda(0);
#pragma unroll
        for (int m2 = 0; m2 < 8; m2++) ldsm4(b[m2], u1 + 256 * m2);
#pragma unroll
        for (int i = 0; i < 8; i++) acc[i][0] = acc[i][1] = acc[i][2] = acc[i][3] = 0.f;
#pragma unroll 1
        for (int j0 = 0; j0 < 8; j0++) {
            k1 += 64; u1 -= 16;
            lda(3);
#pragma unroll
            for (int m = 0; m < 16; m++) {
                mma_bf(acc[m], a[0][0], a[0][1], a[0][2], a[0][3], b[m >> 1][2 * (m & 1)], b[m >> 1][2 * (m & 1) + 1]);
                if (m & 1) ldsm4(b[m >> 1], u1 + 256 * (m >> 1));
            }
            lda(2); lda(1); lda(0);
#pragma unroll
            for (int j1 = 3; j1 > 0; j1--)
#pragma unroll
                for (int m = 0; m + j1 < 16; m++) mma_bf(acc[m + j1], a[j1][0], a[j1][1], a[j1][2], a[j1][3], b[m >> 1][2 * (m & 1)], b[m >> 1][2 * (m & 1) + 1]);
        }
        const uint32_t kv = __byte_perm(lds32(kt + KT_P4 + 152 * 4), 0, 0x1010);
        const uint32_t e0 = kv & ((((unsigned)(d0 - 3) < 2u) ? 0xffffu : 0u) | (((unsigned)(d0 - 4) < 2u) ? 0xffff0000u : 0u));
        const uint32_t e1 = kv & ((((unsigned)(d0 + 5) < 2u) ? 0xffffu : 0u) | (((unsigned)(d0 + 4) < 2u) ? 0xffff0000u : 0u));
        const uint32_t e3 = e0 + oz, e4 = e1 + oz, z2 = oz + oz;
        uint32_t f[2][4];
        ldsm4(f[0], ut + UT_PL - 16 + lane * 16); ldsm4(f[1], ut + UT_PL - 16 + 512 + lane * 16);
#pragma unroll
        for (int m = 1; m < 16; m++) mma_bf(acc[m], a[0][0], a[0][1], a[0][2], a[0][3], b[m >> 1][2 * (m & 1)], b[m >> 1][2 * (m & 1) + 1]);
#pragma unroll
        for (int m = 1; m < 9; m++) mma_bf(acc[m + 7], e0, e1, oz, e3, b[m >> 1][2 * (m & 1)], b[m >> 1][2 * (m & 1) + 1]);
#pragma unroll
        for (int m = 0; m < 8; m++) mma_bf8(acc[m + 8], e4, z2, f[m >> 2][m & 3]);
    }
    TSTAMP(48 + warp);
    uint32_t kb[5][4];
#pragma unroll
    for (int l = 0; l < 5; l++) { const uint4 x = lds128(kt + KT_P4 + (6 + 8 * l + d0) * 16); kb[l][0] = x.x; kb[l][1] = x.y; kb[l][2] = x.z; kb[l][3] = x.w; }
    const uint32_t w0 = band(2 * t, 6 + g, 2), w1 = band(2 * t, 2 + g, 1), w2 = band(2 * t + 8, 6 + g, 2), w3 = band(2 * t + 8, 2 + g, 1);
    const uint32_t a0 = ut + g * 16 + (t == 3 ? UT_PL : 4 + 4 * t), a1 = ut + g * 16 + (t == 3 ? 16 : UT_PL + 4 + 4 * t);
    const uint32_t od = mapa(sb + SC_OUT + rank * OUT_HALF + warp * 288 + g * 32 + (t & 1) * 16, t >> 1), ob = mapa(sb + SC_BAR + 48, t >> 1);
    auto emit = [&](int q) {
        st_async128(od + q * OUT_STAGE, pack_bf16(acc[2 * q][0], acc[2 * q][1]), pack_bf16(acc[2 * q][2], acc[2 * q][3]),
                    pack_bf16(acc[2 * q + 1][0], acc[2 * q + 1][1]), pack_bf16(acc[2 * q + 1][2], acc[2 * q + 1][3]), ob + 8 * q);
    };
    uint32_t x[12][4];
    auto load = [&](int j) { x[j][0] = lds32(a0 + 128 * j - 16); x[j][1] = lds32(a1 + 128 * j - 16); x[j][2] = lds32(a0 + 128 * j); x[j][3] = lds32(a1 + 128 * j); };
    load(0); load(1);
    emit(0); emit(1);
    bar_sync(6 + (warp & 3), 64);
#pragma unroll
    for (int j = 0; j < 12; j++) {
        if (j + 2 < 11) load(j + 2);
        if (j == 10) load(11);
        float X[4], Y[4], Z[4];
        mma_bf0(X, w0, w1, w2, w3, x[j][0], x[j][1]); mma_bf0(Y, w0, w1, w2, w3, x[j][1] + oz, x[j][2] + oz); mma_bf0(Z, w0, w1, w2, w3, x[j][2], x[j][3]);
        const uint32_t x5 = pack_bf16(X[0], X[1]), x3 = pack_bf16(X[2], X[3]), y5 = pack_bf16(Y[0], Y[1]), y3 = pack_bf16(Y[2], Y[3]), z5 = pack_bf16(Z[0], Z[1]), z3 = pack_bf16(Z[2], Z[3]);
        const uint32_t y3c = y3 + oz, y5c = y5 + oz;
#pragma unroll
        for (int l = 0; l < 5; l++) if (j + 4 + l < 16) mma_bf(acc[j + 4 + l], y5, z5, y3, z3, kb[l][0], kb[l][1]);
#pragma unroll
        for (int l = 0; l < 5; l++) if (j + 4 + l < 16) mma_bf(acc[j + 4 + l], x5, y5c, x3, y3c, kb[l][2], kb[l][3]);
        if (j & 1) emit(2 + (j >> 1));
    }
    TSTAMP(56 + warp);
}

__device__ __forceinline__ uint32_t utile_addr(uint32_t sb, int row, int c8) {
    return sb + SC_UTILE + (row >> 9) * 8192 + (((row >> 4) & 3) + 4 * (row & 1) + 8 * ((row >> 7) & 3) + 32 * ((row >> 1) & 7)) * 32 + ((c8 ^ row) & 1) * 16;
}

__device__ __forceinline__ void conv_helper(const Params& p, uint32_t sb, int cb, uint32_t tag) {
    const int hw = warp_id() - 8, lane = threadIdx.x & 31, g = lane >> 2, t = lane & 3, mi = lane >> 3, r8 = lane & 7;
    const int rank = cb & 1, slab = cb >> 1;
    const uint32_t bar_ut = sb + SC_BAR + 32, bar_out = sb + SC_BAR + 48, s_key = sb + SC_BAR + 128;
    {
        const int box = hw >> 1, h = hw & 1;
        const uint32_t src = sb + SC_UTILE + box * 8192 + h * 4096 + (32 * mi + (r8 >> 1) + 4 * (r8 & 1)) * 32;
        const uint32_t so = ((rank ^ r8) & 1) << 4;
        const uint32_t dst = sb + SC_UT + g * UT_STRIDE + 128 + h * UT_PL + (32 * box + 4 * rank + t) * 16;
        const uint32_t rdst = mapa(dst, rank ^ 1), rbar = mapa(bar_ut, rank ^ 1);
        mbar_wait(sb + SC_BAR + 8 * box);
        if (hw == 0) TSTAMP(8);
        uint32_t a[4][4], b[4][4];
#pragma unroll
        for (int k = 0; k < 4; k++) ldsm4t(a[k], src + (so ^ 16) + k * 256);
#pragma unroll
        for (int k = 0; k < 4; k++) ldsm4t(b[k], src + so + k * 256);
#pragma unroll
        for (int k = 0; k < 4; k++) st_async128(rdst + k * 128, a[k][0], a[k][1], a[k][2], a[k][3], rbar);
#pragma unroll
        for (int k = 0; k < 4; k++) sts128(dst + k * 128, b[k][0], b[k][1], b[k][2], b[k][3]);
        __syncwarp();
        if (lane == 0) mbar_arrive(bar_ut);
        if (hw == 0) TSTAMP(9);
    }
    if (hw == 4) {
        uint32_t key;
        for (int it = 0;;) {
            key = ld_rlx32(&p.scr->sel[r8]);
            if (__all_sync(0xffffffffu, ((key >> 11) & 3u) == tag)) break;
            POLL_GUARD(it);
            __nanosleep(200);
        }
        if (lane < 8) sts32(s_key + 4 * lane, key);
        TSTAMP(10);
    }
    bar_sync(1, 256);
    if (hw < 4) {
        const uint32_t last = lds32(s_key + 28), tg = ((last >> 11) & 3u) << 14;
        const int par = hw >> 1, i0 = 4 * (hw & 1);
        const int row0 = 256 * par + 128 * (g >> 2) + 64 * rank + 32 * (t >> 1) + 16 * (g & 1) + 8 * ((g >> 1) & 1) + i0;
        uint4 r[4];
        for (int it = 0;;) {
            uint32_t bad = 0;
#pragma unroll
            for (int k = 0; k < 4; k++) { r[k] = ld_rlx128(&p.scr->rec[row0 + 512 * k]); }
#pragma unroll
            for (int k = 0; k < 4; k++) bad |= (r[k].x ^ tg) | (r[k].y ^ tg) | (r[k].z ^ tg) | (r[k].w ^ tg);
            if ((bad & 0xc000u) == 0) break;
            POLL_GUARD(it);
        }
        if (hw == 0) TSTAMP(11);
        const uint32_t thr = last & ~0x1800u;
        const uint32_t ya = sb + SC_OUT + par * OUT_STAGE + ((r8 >> 1) & 1) * OUT_HALF + (2 * mi + (r8 & 1)) * 288 + (2 * i0 + (r8 >> 2)) * 16;
        const uint32_t ua = utile_addr(sb, row0, t & 1);
        __nv_bfloat16* op = p.out + row0 * DM + 16 * slab + 8 * (t & 1);
#pragma unroll
        for (int k = 0; k < 4; k++) {
            const uint32_t rr[4] = {r[k].x, r[k].y, r[k].z, r[k].w};
            uint4 ou[4];
            uint32_t gg[4];
#pragma unroll
            for (int i = 0; i < 4; i++) {
                gg[i] = __byte_perm(rr[i], 0, 0x1010) & 0x3fff3fffu;
                const uint32_t om = hsub2(0x3f803f80u, gg[i]);
                const uint4 u4 = lds128((ua ^ ((i & 1) * 16)) + k * 8192 + (i & 1) * 128 + (i >> 1) * 1024);
                ou[i] = make_uint4(hmul2(om, u4.x), hmul2(om, u4.y), hmul2(om, u4.z), hmul2(om, u4.w));
            }
            mbar_wait(bar_out + 8 * par + 16 * k);
            if (hw == 2) TSTAMP(20 + k); if (hw == 0) TSTAMP(16 + k);
            uint32_t y[4][4];
#pragma unroll
            for (int i = 0; i < 4; i++) ldsm4t(y[i], ya + 2 * k * OUT_STAGE + 32 * i);
#pragma unroll
            for (int i = 0; i < 4; i++) {
                const uint4 o = make_uint4(hfma2(gg[i], y[i][0], ou[i].x), hfma2(gg[i], y[i][1], ou[i].y), hfma2(gg[i], y[i][2], ou[i].z), hfma2(gg[i], y[i][3], ou[i].w));
                if (((rr[i] & 0xffff0000u) | (uint32_t)(2047 - 512 * k - i - row0)) < thr) *(uint4*)(op + (512 * k + i) * DM) = o;
            }
        }
        if (hw == 0) TSTAMP(6); if (hw == 2) TSTAMP(7);
    } else {
        const int gw = hw - 4, ht = 32 * gw + lane, tok = ht >> 4, c = ht & 15;
        const uint32_t key = lds32(s_key + 4 * tok);
        tag = (key >> 11) & 3u;
        const int row = key_row(key);
        const bool own = ((row >> 6) & 1) == rank, take = ((key_row(lds32(s_key + 4 * g)) >> 6) & 1) == rank;
        if (!__any_sync(0xffffffffu, take)) return;
        uint32_t rc = 0;
        if (own) for (int it = 0;;) { rc = ld_rlx32(&p.scr->rec[row]); if (((rc >> 14) & 3u) == tag) break; POLL_GUARD(it); }
        const float gt = bf_lo(rc & 0x3fffu), om = rbf(1.f - gt), rs = rbf(sigmoidf_(key_val(key)));
        const float xv = bf_lo(lds16((utile_addr(sb, row, c >> 3)) + (c & 7) * 2));
        const uint4* src = p.scr->part + (slab * NFFN + 15 * gw) * 32;
        for (int it = 0;;) {
            const uint32_t w = ld_rlx32(src + min(lane, 14) * 32);
            if (__any_sync(0xffffffffu, (w & 3u) == tag)) break;
            POLL_GUARD(it);
            __nanosleep(100);
        }
        if (gw == 0) TSTAMP(12);
        uint4 v[15];
#pragma unroll
        for (int k = 0; k < 15; k++) v[k] = make_uint4(take ? 0u : tag, 0u, 0u, 0u);
        for (int it = 0;;) {
#pragma unroll
            for (int k = 0; k < 15; k++) if ((v[k].x & 3u) != tag) v[k] = ld_pkt(src + k * 32 + lane);
            uint32_t bad = 0;
#pragma unroll
            for (int k = 0; k < 15; k++) bad |= v[k].x ^ tag;
            if (__all_sync(0xffffffffu, (bad & 3u) == 0)) break;
            POLL_GUARD(it);
        }
        float s0 = 0.f, s1 = 0.f, s2 = 0.f, s3 = 0.f;
#pragma unroll
        for (int k = 0; k < 15; k++) { s0 += __uint_as_float(v[k].x); s1 += __uint_as_float(v[k].y); s2 += __uint_as_float(v[k].z); s3 += __uint_as_float(v[k].w); }
        sts128(sb + SC_RED + ht * 16, __float_as_uint(s0), __float_as_uint(s1), __float_as_uint(s2), __float_as_uint(s3));
        bar_sync(10, 128);
        if (gw == 0) TSTAMP(13);
        if (own) {
            const uint32_t ra = sb + SC_RED + (tok * 4 + ((c & 7) >> 1)) * 16 + ((c >> 3) * 2 + (c & 1)) * 4;
            const float y = rbf((__uint_as_float(lds32(ra)) + __uint_as_float(lds32(ra + 512))) + (__uint_as_float(lds32(ra + 1024)) + __uint_as_float(lds32(ra + 1536))));
            const float b = rbf(xv + rbf(y * rs));
            mbar_wait(bar_out + 8 * (row >> 8));
            const float a = bf_lo(lds16(sb + SC_OUT + (row >> 8) * OUT_STAGE + (c >> 3) * OUT_HALF + (c & 7) * 288 + (row & 7) * 32 + ((row >> 5) & 1) * 16
                                        + ((row >> 7) & 1) * 8 + ((row >> 3) & 1) * 4 + ((row >> 4) & 1) * 2));
            *(unsigned short*)(p.out + row * DM + 16 * slab + c) = (unsigned short)pack_bf16(gt * a + rbf(om * b), 0.f);
        }
        if (gw == 0) TSTAMP(14);
    }
}

__device__ __forceinline__ void conv_setup(const Params& p, const CUtensorMap* mU, uint32_t sb, int cb, uint32_t t0) {
    const int hw = warp_id() - 8, lane = threadIdx.x & 31, rank = cb & 1;
    const uint32_t bar_tk = sb + SC_BAR + 40, s_tk = sb + SC_BAR + 160;
    uint32_t tag = 0;
    if (lane == 0) {
        const uint32_t bo = sb + SC_BAR + 48 + 8 * hw, b2 = sb + SC_BAR + 8 * hw;
        if (hw == 4) { mbar_init(b2, 9); mbar_init(bar_tk, 1); }
        if (hw < 4) mbar_init(b2, 1);
        mbar_init(bo, 1);
        mbar_fence_init();
        if (hw < 5) mbar_expect(b2, hw < 4 ? 8192 : 16384);
        if (UDELAY) spin_until(t0, UDELAY);
        if (hw < 4) tma5d(sb + SC_UTILE + hw * 8192, mU, 16 * (cb >> 1), 4 * rank, 0, 4 * hw, 0, b2);
        mbar_expect(bo, 4096);
        if (hw == 4) tag = take_ticket(&p.scr->launch);
    }
    __syncwarp();
    cluster_arrive_relaxed();
    if (hw == 4) {
        tag = tag_of(__shfl_sync(0xffffffffu, tag, 0));
        if (lane == 0) { sts32(s_tk, tag); mbar_arrive(bar_tk); }
    }
    cluster_wait();
    conv_helper(p, sb, cb, tag);
}

__device__ __forceinline__ void conv_main(const Params& p, uint32_t sb, int cb, uint32_t t0, float (&kv)[21]) {
    const int warp = warp_id(), lane = threadIdx.x & 31;
    if (warp >= 4) {
        mbar_wait(sb + SC_BAR + 40);
        const uint32_t tag = lds32(sb + SC_BAR + 160);
        const uint4* src = p.scr->kx + (4 * cb + warp - 4) * 96 + lane;
        while (clk() - t0 < KDELAY) __nanosleep(50);
        uint4 x[3];
        for (int it = 0;;) {
            x[0] = ld_pkt(src); x[1] = ld_pkt(src + 32); x[2] = ld_pkt(src + 64);
            if (__all_sync(0xffffffffu, (((x[0].w ^ tag) | (x[1].w ^ tag) | (x[2].w ^ tag)) & 0xffffu) == 0)) break;
            POLL_GUARD(it);
        }
#pragma unroll
        for (int i = 0; i < 3; i++) {
            kv[7 * i] = bf_lo(x[i].x); kv[7 * i + 1] = bf_hi(x[i].x); kv[7 * i + 2] = bf_lo(x[i].y); kv[7 * i + 3] = bf_hi(x[i].y);
            kv[7 * i + 4] = bf_lo(x[i].z); kv[7 * i + 5] = bf_hi(x[i].z); kv[7 * i + 6] = bf_hi(x[i].w);
        }
        if (warp == 4) TSTAMP(5);
    }
    ktables(kv, sb + SC_KT + warp * KT_BYTES);
    TSTAMP(32 + warp);
    conv_warp(sb, cb & 1);
}

__device__ __forceinline__ void ffn_cta(const Params& p, const CUtensorMap* mR, const CUtensorMap* mG64, const CUtensorMap* mU64, const CUtensorMap* mG16,
                                        const CUtensorMap* mU16, const CUtensorMap* mWd, uint32_t sb, int f, uint32_t t0, const float (&kv)[21], int ci) {
    const int tid = threadIdx.x, warp = warp_id(), lane = tid & 31, g = lane >> 2, t = lane & 3, mi = lane >> 3, r8 = lane & 7;
    const bool wide = f < 48;
    const int nunit = wide ? 10 : 8;
    const uint32_t bar_w = sb + SF_BAR, bar_d = bar_w + 72, bar_r = bar_w + 112, bar_sel = bar_w + 152, bar_free = bar_w + 160, bar_kg = bar_w + 184, bar_tk = bar_w + 192;
    uint32_t tag;
    uint4* const pdst = p.scr->part + (3 * warp * NFFN + f) * 32 + lane;
    auto clear_part = [&]() { st_pkt(pdst, 0, 0, 0, 0); st_pkt(pdst + NFFN * 32, 0, 0, 0, 0); st_pkt(pdst + 2 * NFFN * 32, 0, 0, 0, 0); };
    if (warp == 13) {
        if (lane == 0) {
#pragma unroll
            for (int i = 0; i < 14; i++) mbar_init(bar_w + 8 * i, 1);
            mbar_init(bar_sel, f >= 44 ? 5 : 4); mbar_init(bar_free, nunit); mbar_init(bar_free + 8, nunit); mbar_init(bar_free + 16, nunit); mbar_init(bar_kg, nunit / 2); mbar_init(bar_tk, 1);
            mbar_fence_init();
        }
        __syncwarp();
        cluster_arrive_relaxed();
        cluster_wait();
        if (lane == 0) {
            spin_until(t0, FDELAY);
            prefetch_map(mG64); prefetch_map(mU64); prefetch_map(mG16); prefetch_map(mU16); prefetch_map(mWd);
            spin_until(t0, WDELAY);
#pragma unroll 1
            for (int n = 0; n < 9; n++) {
                if (n >= WWIN) { int it = 0; while (!mbar_test(bar_w + 8 * (n - WWIN)) && !mbar_test(bar_free)) { SPIN; POLL_GUARD(it); } }
                if (n == 4) mbar_wait(bar_kg);
                if (n == 8) mbar_wait(bar_sel);
                const uint32_t b = bar_w + 8 * n, d = sb + n * PIECE;
                mbar_expect(b, wide ? PIECE : 16384);
                tma2d(d, mG64, 64 * f, 64 * n, b); tma2d(d + 8192, mU64, 64 * f, 64 * n, b);
                if (wide) { tma2d(d + 16384, mG16, 3840 + 16 * f, 64 * n, b); tma2d(d + 18432, mU16, 3840 + 16 * f, 64 * n, b); }
            }
            TSTAMP(10);
#pragma unroll 1
            for (int i = 0; i < nunit / 2; i++) {
                if (i < 2) { int it = 0; while (!mbar_test(bar_w + 8 * (9 + i - WWIN)) && !mbar_test(bar_free)) { SPIN; POLL_GUARD(it); } }
                else mbar_wait(bar_free + 8 * (i - 2));
                mbar_expect(bar_d + 8 * i, 18432);
                tma2d(i < 2 ? sb + SF_R + i * 18432 : sb + (i - 2) * PIECE, mWd, 0, 9 * (i < 4 ? 64 * f + 16 * i : 3840 + 16 * f), bar_d + 8 * i);
            }
            TSTAMP(11);
        }
        return;
    }
    if (warp >= 10) {
        const int ng = f >= 44 ? 5 : 4, r0 = f >= 44 ? 1408 + 40 * (f - 44) : 32 * f;
        const int grp = warp == 12 ? 4 : warp < 12 ? warp - 10 : warp - 12;
        const uint32_t rows = grp < 4 ? sb + SF_R + grp * 9216 : sb + SF_R4;
        const int i = 32 * grp + lane;
        if (lane == 0) { mbar_init(bar_r + 8 * grp, 1); mbar_fence_init(); mbar_expect(bar_r + 8 * grp, 9216); }
        __syncwarp();
        cluster_arrive_relaxed();
        if (grp == 4) {
#pragma unroll 1
            for (int k = lane; k < 256; k += 32) sts128(sb + SF_LIST + k * 16, 0, 0, 0, 0);
        }
        uint4 w;
        spin_until(t0, RDELAY);
        if (lane == 0 && grp < ng) tma2d(rows, mR, 0, 9 * (r0 + 8 * grp), bar_r + 8 * grp);
        if (i < 144) w = ldg128((const uint4*)(i < 72 ? p.wr : p.gatew - DM) + i);
        if (i == 159) w.x = take_ticket(&p.scr->launch);
        if (grp < ng && t == 0) st_rlx32(&p.scr->rec[r0 + 8 * grp + g], 0);
        if (i < 144) sts128(sb + SF_WR + i * 16, w.x, w.y, w.z, w.w);
        if (i == 159) sts64(sb + SF_CNT, 0, tag_of(w.x));
        if (warp == 12) TSTAMP(16); if (warp == 10) TSTAMP(17);
        cluster_wait();
        bar_sync(10, 160);
        if (i == 159) mbar_arrive(bar_tk);
        if (grp < ng) {
            uint32_t wv[9][4];
            const uint32_t wa = sb + SF_WR + ((r8 >> 1) & 1) * 1152 + (2 * mi + (r8 & 1)) * 16;
#pragma unroll
            for (int k = 0; k < 9; k++) ldsm4(wv[k], wa + 128 * k);
            tag = lds32(sb + SF_TK);
            float c[3][4];
            mbar_wait(bar_r + 8 * grp);
            if (warp == 10) TSTAMP(1);
#pragma unroll
            for (int k = 0; k < 18; k++) {
                const int line = 9 * r8 + (k >> 1);
                uint32_t a[4];
                ldsm4(a, rows + line * 128 + ((((4 * k + mi) ^ line) & 7) << 4));
                if (k < 3) mma_bf0(c[k], a[0], a[1], a[2], a[3], wv[k >> 1][2 * (k & 1)], wv[k >> 1][2 * (k & 1) + 1]);
                else mma_bf(c[k % 3], a[0], a[1], a[2], a[3], wv[k >> 1][2 * (k & 1)], wv[k >> 1][2 * (k & 1) + 1]);
            }
            const float s = (c[0][0] + c[0][3]) + (c[1][0] + c[1][3]) + (c[2][0] + c[2][3]);
            const uint32_t gg = __shfl_down_sync(0xffffffffu, pack_bf16(sigmoidf_(rbf(s)), 0.f), 1);
            uint32_t rb = pack_bf16(0.f, s);
            rb = (rb & 0x80000000u) ? ~rb : (rb | 0x80000000u);
            if (t == 0) st_rlx32(&p.scr->rec[r0 + 8 * grp + g], (rb & 0xffff0000u) | (tag << 14) | (gg & 0x3fffu));
            if (lane == 0) { sts32(sb + SF_CLK, clk()); mbar_arrive(bar_sel); }
            if (warp == 10) TSTAMP(2);
        }
        if (warp >= 12) return;
        clear_part();
    } else {
        if (warp >= nunit) { cluster_arrive_relaxed(); cluster_wait(); }
        mbar_wait(bar_tk);
        tag = lds32(sb + SF_TK);
        if (warp < nunit / 2) {
            uint4* const kdst = p.scr->kx + ci * 96 + lane;
#pragma unroll
            for (int i = 0; i < 3; i++)
                st_pkt(kdst + 32 * i, pack_bf16(kv[7 * i], kv[7 * i + 1]), pack_bf16(kv[7 * i + 2], kv[7 * i + 3]), pack_bf16(kv[7 * i + 4], kv[7 * i + 5]), pack_bf16(0.f, kv[7 * i + 6]) | tag);
            __syncwarp();
            if (lane == 0) mbar_arrive(bar_kg);
            if (warp == 0) TSTAMP(12); if (warp == 2) TSTAMP(13);
        }
        clear_part();
        if (warp < 8) {
            uint32_t k[8];
            const uint32_t tg = tag << 14;
            mbar_wait(bar_sel);
            spin_until(lds32(sb + SF_CLK), PDELAY);
            for (int it = 0;;) {
                const uint4 a = ld_rlx128(&p.scr->rec[4 * tid]), b = ld_rlx128(&p.scr->rec[1024 + 4 * tid]);
                k[0] = a.x; k[1] = a.y; k[2] = a.z; k[3] = a.w; k[4] = b.x; k[5] = b.y; k[6] = b.z; k[7] = b.w;
                if (__all_sync(0xffffffffu, (((a.x ^ tg) | (a.y ^ tg) | (a.z ^ tg) | (a.w ^ tg) | (b.x ^ tg) | (b.y ^ tg) | (b.z ^ tg) | (b.w ^ tg)) & 0xc000u) == 0)) break;
                POLL_GUARD(it);
            }
            if (warp == 0) TSTAMP(3);
#pragma unroll
            for (int i = 0; i < 8; i++) k[i] = (k[i] & 0xffff0000u) | (uint32_t)(2047 - 1024 * (i >> 2) - (i & 3) - 4 * tid);
            const uint32_t m0 = __reduce_max_sync(0xffffffffu, max(max(k[0], k[1]), max(k[2], k[3]))), m1 = __reduce_max_sync(0xffffffffu, max(max(k[4], k[5]), max(k[6], k[7])));
            if (lane == 0) sts64(sb + SF_MAX + warp * 8, m0, m1);
            bar_sync(7, 256);
            uint32_t thr;
            {
                const uint32_t m = lds32(sb + SF_MAX + (lane & 15) * 4);
                int rk = 0;
#pragma unroll
                for (int i = 0; i < 4; i++) { const uint4 x = lds128(sb + SF_MAX + 16 * i); rk += (x.x > m) + (x.y > m) + (x.z > m) + (x.w > m); }
                thr = __reduce_max_sync(0xffffffffu, rk == 7 ? m : 0u);
            }
#pragma unroll
            for (int i = 0; i < 8; i++)
                if (k[i] >= thr) { uint32_t s; asm volatile("atom.shared.add.u32 %0, [%1], 1;" : "=r"(s) : "r"(sb + SF_CNT) : "memory"); sts32(sb + SF_LIST + 4 * s, k[i]); }
            bar_sync(7, 256);
            const int n = lds32(sb + SF_CNT);
            uint32_t key = 0;
#pragma unroll 1
            for (int base = 0; base < n; base += 32) {
                const uint32_t m = lds32(sb + SF_LIST + (base + lane) * 4);
                int rk = 0;
#pragma unroll 1
                for (int i = 0; i < n; i += 8) {
                    const uint4 x = lds128(sb + SF_LIST + 4 * i), y = lds128(sb + SF_LIST + 4 * i + 16);
                    rk += (x.x > m) + (x.y > m) + (x.z > m) + (x.w > m) + (y.x > m) + (y.y > m) + (y.z > m) + (y.w > m);
                }
                if (rk == warp && base + lane < n) key = m;
            }
            key = __reduce_max_sync(0xffffffffu, key);
            if (warp == 0) TSTAMP(4);
            const uint4* xr = (const uint4*)(p.u + key_row(key) * DM);
            const uint4 x0 = ldg128(xr + lane), x1 = ldg128(xr + 32 + lane), x2 = ldg128(xr + 64 + r8);
            if (lane == 0) sts32(sb + SF_SEL + warp * 4, key | (tag << 11));
            bar_sync(7, 256);
            if (f == 0 && tid < 8) st_rlx32(&p.scr->sel[tid], lds32(sb + SF_SEL + tid * 4));
            const uint32_t xd = sb + SF_XS + warp * 1168 + lane * 16;
            sts128(xd, x0.x, x0.y, x0.z, x0.w); sts128(xd + 512, x1.x, x1.y, x1.z, x1.w);
            if (lane < 8) sts128(xd + 1024, x2.x, x2.y, x2.z, x2.w);
        }
        if (warp < nunit) {
            bar_sync(8, 32 * nunit);
            if (warp == 0) TSTAMP(5);
            const int kr = 8 * (mi >> 1) + r8;
            uint32_t wa = warp < 8 ? sb + (mi & 1) * 8192 + kr * 128 + ((warp ^ r8) << 4) : sb + 16384 + (mi & 1) * 2048 + kr * 32 + (((warp ^ (r8 >> 2)) & 1) << 4);
            const uint32_t ws = warp < 8 ? 2048 : 512;
            uint32_t xa = sb + SF_XS + r8 * 1168 + mi * 16;
            float c0[4] = {0.f, 0.f, 0.f, 0.f}, c1[4] = {0.f, 0.f, 0.f, 0.f};
#pragma unroll 1
            for (int n = 0; n < 9; n++) {
                uint32_t x[2][4], a[4][4];
                ldsm4(x[0], xa); ldsm4(x[1], xa + 64);
                mbar_wait(bar_w + 8 * n);
#pragma unroll
                for (int s = 0; s < 4; s++) ldsm4t(a[s], wa + s * ws);
                mma_bf(c0, a[0][0], a[0][1], a[0][2], a[0][3], x[0][0], x[0][1]);
                mma_bf(c1, a[1][0], a[1][1], a[1][2], a[1][3], x[0][2], x[0][3]);
                mma_bf(c0, a[2][0], a[2][1], a[2][2], a[2][3], x[1][0], x[1][1]);
                mma_bf(c1, a[3][0], a[3][1], a[3][2], a[3][3], x[1][2], x[1][3]);
                if (n < 3) {
                    asm volatile("" :: "r"(a[0][0]), "r"(a[1][0]), "r"(a[2][0]), "r"(a[3][0]) : "memory");
                    __syncwarp();
                    if (lane == 0) mbar_arrive(bar_free + 8 * n);
                }
                wa += PIECE; xa += 128;
            }
            if (warp == 0) TSTAMP(6);
            float h[2];
#pragma unroll
            for (int e = 0; e < 2; e++) {
                const float gv = rbf(c0[e] + c1[e]), uv = rbf(c0[2 + e] + c1[2 + e]);
                h[e] = rbf(gv * sigmoidf_(gv)) * uv;
            }
            uint32_t hp = pack_bf16(h[0], h[1]);
            asm volatile("movmatrix.sync.aligned.m8n8.trans.b16 %0, %0;" : "+r"(hp));
            sts32(sb + SF_H + (warp >> 1) * 256 + lane * 8 + (warp & 1) * 4, hp);
        }
    }
    bar_sync(9, 384);
    tag = lds32(sb + SF_TK);
    float d[6][4];
    uint32_t off[3];
#pragma unroll
    for (int j = 0; j < 3; j++) {
        const int tile = 3 * warp + j, line = 9 * (8 * (mi & 1) + r8) + (tile >> 2);
        off[j] = line * 128 + ((((2 * tile + (mi >> 1)) ^ line) & 7) << 4);
    }
#pragma unroll
    for (int j = 0; j < 6; j++) d[j][0] = d[j][1] = d[j][2] = d[j][3] = 0.f;
#pragma unroll 1
    for (int i = 0; i < nunit / 2; i++) {
        const uint2 hv = lds64(sb + SF_H + i * 256 + lane * 8);
        const uint32_t base = i < 2 ? sb + SF_R + i * 18432 : sb + (i - 2) * PIECE;
        mbar_wait(bar_d + 8 * i);
        uint32_t a[3][4];
#pragma unroll
        for (int j = 0; j < 3; j++) ldsm4t(a[j], base + off[j]);
#pragma unroll
        for (int j = 0; j < 3; j++) { mma_bf(d[2 * j], hv.x, 0u, hv.y, 0u, a[j][0], a[j][1]); mma_bf(d[2 * j + 1], hv.x, 0u, hv.y, 0u, a[j][2], a[j][3]); }
    }
    if (warp == 0) TSTAMP(7);
#pragma unroll
    for (int j = 0; j < 3; j++) {
        st_pkt(pdst + j * NFFN * 32, (__float_as_uint(d[2 * j][0]) & ~3u) | tag, __float_as_uint(d[2 * j][1]), __float_as_uint(d[2 * j + 1][0]), __float_as_uint(d[2 * j + 1][1]));
    }
    if (warp == 0) TSTAMP(8);
}

__global__ void __cluster_dims__(2, 1, 1) __launch_bounds__(NTHR, 1)
fused_kernel(const Params p, const __grid_constant__ CUtensorMap mU, const __grid_constant__ CUtensorMap mR, const __grid_constant__ CUtensorMap mG64,
             const __grid_constant__ CUtensorMap mU64, const __grid_constant__ CUtensorMap mG16, const __grid_constant__ CUtensorMap mU16,
             const __grid_constant__ CUtensorMap mWd) {
    extern __shared__ __align__(1024) uint8_t smem_raw[];
    const uint32_t sb = smem_u32(smem_raw);
    const uint32_t t0 = clk();
    const int bx = blockIdx.x;
    const int lane = threadIdx.x & 31, f = bx - FFN0, cb = bx < FFN0 ? bx : bx - NFFN;
    const bool ffn = (unsigned)f < NFFN;
    const int nch = (unsigned)f < 48 ? 5 : 4, c0 = ffn ? (nch == 5 ? 5 * f : 4 * f + 48) : 4 * cb;
    KParams kp;
    {
        const int w = threadIdx.x >> 5, h = w >= nch, c = c0 + w - nch * h;
        if (w < 2 * nch) kp = kload(p, 2 * (c & ~3) + (ffn ? 4 : 0) + (c & 3), h);
    }
    const int warp = warp_id(), half = warp >= nch, j = warp - nch * half, ci = c0 + j;
    float kv[21];
    if (warp < 2 * nch) {
        const uint32_t stage = sb + (ffn ? SF_STG : SC_STG);
        cluster_arrive_relaxed();
        if (!ffn) {
            if (lane < 16) sts128(sb + SC_UT + warp * UT_STRIDE + (lane >> 3) * UT_PL + (lane & 7) * 16, 0, 0, 0, 0);
            if (lane < 28) sts128(sb + SC_KT + warp * KT_BYTES + 16 * (lane < 4 ? lane : lane < 16 ? 128 + lane : 158 + lane), 0, 0, 0, 0);
        }
        if (f == 0 && threadIdx.x < 8) st_rlx32(&p.scr->sel[lane], 0);
        float fin;
        kgen(kp, stage + warp * KG_STAGE, kv, fin, sb);
        cluster_wait();
        if (half) ksend(kv, fin, stage + warp * KG_STAGE, 2 + j);
        else krecv(kv, fin, stage + (warp + nch) * KG_STAGE, 2 + j, kp.dskip);
    }
    if (ffn) ffn_cta(p, &mR, &mG64, &mU64, &mG16, &mU16, &mWd, sb, f, t0, kv, ci);
    else if (warp < 8) conv_main(p, sb, cb, t0, kv);
    else conv_setup(p, &mU, sb, cb, t0);
}

typedef CUresult (*EncodeFn)(CUtensorMap*, CUtensorMapDataType, cuuint32_t, void*, const cuuint64_t*, const cuuint64_t*, const cuuint32_t*, const cuuint32_t*,
                             CUtensorMapInterleave, CUtensorMapSwizzle, CUtensorMapL2promotion, CUtensorMapFloatOOBfill);

CUtensorMap make_map(EncodeFn fn, const void* base, uint64_t inner, uint64_t outer, uint32_t bi, uint32_t bo, CUtensorMapSwizzle sw,
                     CUtensorMapL2promotion pr = CU_TENSOR_MAP_L2_PROMOTION_NONE) {
    CUtensorMap m;
    cuuint64_t dims[2] = {inner, outer};
    cuuint64_t strides[1] = {inner * 2};
    cuuint32_t box[2] = {bi, bo};
    cuuint32_t es[2] = {1, 1};
    fn(&m, CU_TENSOR_MAP_DATA_TYPE_BFLOAT16, 2, (void*)base, dims, strides, box, es, CU_TENSOR_MAP_INTERLEAVE_NONE, sw, pr, CU_TENSOR_MAP_FLOAT_OOB_FILL_NONE);
    return m;
}

}

extern "C" void kernel_launch(void* const* d_in, const int* in_sizes, int n_in, void* d_out, int out_size) {
    (void)in_sizes; (void)n_in; (void)out_size;
    static EncodeFn fn = nullptr;
    static Scratch* scr = nullptr;
    if (!fn) {
        void* ptr = nullptr; cudaDriverEntryPointQueryResult qr;
        cudaGetDriverEntryPoint("cuTensorMapEncodeTiled", &ptr, cudaEnableDefault, &qr);
        fn = (EncodeFn)ptr;
        cudaGetSymbolAddress((void**)&scr, g_scr);
        cudaFuncSetAttribute(fused_kernel, cudaFuncAttributeMaxDynamicSharedMemorySize, SMEM_BYTES);
    }
    typedef const __nv_bfloat16* bp;
    Params p;
    p.u = (bp)d_in[0]; p.Are = (bp)d_in[1]; p.Aim = (bp)d_in[2]; p.Bre = (bp)d_in[3]; p.Bim = (bp)d_in[4]; p.Cre = (bp)d_in[5]; p.Cim = (bp)d_in[6];
    p.logdt = (bp)d_in[7]; p.Dskip = (bp)d_in[8]; p.wr = (bp)d_in[10]; p.gatew = (bp)d_in[14];
    p.out = (__nv_bfloat16*)d_out; p.scr = scr;
    CUtensorMap mU;
    {
        cuuint64_t dims[5] = {DM, 8, 2, L_SEQ / 128, 8};
        cuuint64_t strides[4] = {16 * DM * 2, DM * 2, 128 * DM * 2, 2 * DM * 2};
        cuuint32_t box[5] = {16, 4, 2, 4, 8};
        cuuint32_t es[5] = {1, 1, 1, 1, 1};
        fn(&mU, CU_TENSOR_MAP_DATA_TYPE_BFLOAT16, 5, d_in[0], dims, strides, box, es, CU_TENSOR_MAP_INTERLEAVE_NONE, CU_TENSOR_MAP_SWIZZLE_32B,
           CU_TENSOR_MAP_L2_PROMOTION_NONE, CU_TENSOR_MAP_FLOAT_OOB_FILL_NONE);
    }
    const CUtensorMap mR = make_map(fn, d_in[0], 64, L_SEQ * 9, 64, 72, CU_TENSOR_MAP_SWIZZLE_128B);
    const CUtensorMap mG64 = make_map(fn, d_in[11], FF, DM, 64, 64, CU_TENSOR_MAP_SWIZZLE_128B);
    const CUtensorMap mU64 = make_map(fn, d_in[12], FF, DM, 64, 64, CU_TENSOR_MAP_SWIZZLE_128B);
    const CUtensorMap mG16 = make_map(fn, d_in[11], FF, DM, 16, 64, CU_TENSOR_MAP_SWIZZLE_32B, CU_TENSOR_MAP_L2_PROMOTION_L2_128B);
    const CUtensorMap mU16 = make_map(fn, d_in[12], FF, DM, 16, 64, CU_TENSOR_MAP_SWIZZLE_32B, CU_TENSOR_MAP_L2_PROMOTION_L2_128B);
    const CUtensorMap mWd = make_map(fn, d_in[13], 64, FF * 9, 64, 144, CU_TENSOR_MAP_SWIZZLE_128B);
    fused_kernel<<<NCTA, NTHR, SMEM_BYTES>>>(p, mU, mR, mG64, mU64, mG16, mU16, mWd);
}
```

```cpp
#include <cuda_runtime.h>
#include <cuda_bf16.h>
#include <cuda_fp16.h>
#include <cuda.h>
#include <stdint.h>

#define RDELAY 1000
#define UDELAY 500
#define WDELAY 1800
#define PDELAY 900
#define KDELAY 6400
#define SPIN
#define FDELAY 600
#define DUPA lds32v(k1 + 512 * j1)
#define PACE 40
#define VDELAY 1000
#define WWIN 3

namespace {

#define JBAR 0
#define UNR 8
constexpr int DUNR = UNR;
constexpr int L_SEQ = 2048, DM = 576, NST = 128, FF = 4608;
constexpr int NCTA = 132, NFFN = 60, FFN0 = 8, NTHR = 512;

struct Scratch {
    unsigned launch; unsigned pad0[31];
    uint32_t sel[32];
    uint32_t rec[L_SEQ];
    uint4 kx[288 * 4 * 32];
    uint4 part[36 * NFFN * 32];
};
__device__ Scratch g_scr;

struct Params {
    const __nv_bfloat16 *Are, *Aim, *Bre, *Bim, *Cre, *Cim, *logdt, *Dskip, *u, *wr, *gatew;
    __nv_bfloat16* out;
    Scratch* scr;
};

__device__ __forceinline__ uint32_t smem_u32(const void* p) { return (uint32_t)__cvta_generic_to_shared(p); }
__device__ __forceinline__ uint32_t pack_bf16(float lo, float hi) { uint32_t r; asm("cvt.rn.bf16x2.f32 %0, %1, %2;" : "=r"(r) : "f"(hi), "f"(lo)); return r; }
__device__ __forceinline__ uint32_t pack_f16(float lo, float hi) { uint32_t r; asm("cvt.rn.f16x2.f32 %0, %1, %2;" : "=r"(r) : "f"(hi), "f"(lo)); return r; }
__device__ __forceinline__ float bf_lo(uint32_t w) { return __uint_as_float(w << 16); }
__device__ __forceinline__ float bf_hi(uint32_t w) { return __uint_as_float(w & 0xffff0000u); }
__device__ __forceinline__ uint32_t cvt_bf16(float x) { uint32_t r; asm volatile("cvt.rn.bf16x2.f32 %0, %1, %1;" : "=r"(r) : "f"(x)); return r; }
__device__ __forceinline__ float rbf(float x) { return bf_lo(pack_bf16(x, 0.f)); }
__device__ __forceinline__ uint32_t hmul2(uint32_t a, uint32_t b) { __nv_bfloat162 r = __hmul2_rn(*(__nv_bfloat162*)&a, *(__nv_bfloat162*)&b); return *(uint32_t*)&r; }
__device__ __forceinline__ uint32_t hadd2(uint32_t a, uint32_t b) { __nv_bfloat162 r = __hadd2_rn(*(__nv_bfloat162*)&a, *(__nv_bfloat162*)&b); return *(uint32_t*)&r; }
__device__ __forceinline__ uint32_t hfma2(uint32_t a, uint32_t b, uint32_t c) { uint32_t r; asm("fma.rn.bf16x2 %0, %1, %2, %3;" : "=r"(r) : "r"(a), "r"(b), "r"(c)); return r; }
__device__ __forceinline__ uint32_t hsub2(uint32_t a, uint32_t b) { __nv_bfloat162 r = __hsub2_rn(*(__nv_bfloat162*)&a, *(__nv_bfloat162*)&b); return *(uint32_t*)&r; }
__device__ __forceinline__ void mma_bf(float (&c)[4], uint32_t a0, uint32_t a1, uint32_t a2, uint32_t a3, uint32_t b0, uint32_t b1) {
    asm("mma.sync.aligned.m16n8k16.row.col.f32.bf16.bf16.f32 {%0,%1,%2,%3}, {%4,%5,%6,%7}, {%8,%9}, {%0,%1,%2,%3};"
        : "+f"(c[0]), "+f"(c[1]), "+f"(c[2]), "+f"(c[3]) : "r"(a0), "r"(a1), "r"(a2), "r"(a3), "r"(b0), "r"(b1));
}
__device__ __forceinline__ void mma_bf0(float (&c)[4], uint32_t a0, uint32_t a1, uint32_t a2, uint32_t a3, uint32_t b0, uint32_t b1) {
    asm("mma.sync.aligned.m16n8k16.row.col.f32.bf16.bf16.f32 {%0,%1,%2,%3}, {%4,%5,%6,%7}, {%8,%9}, {%10,%10,%10,%10};"
        : "=f"(c[0]), "=f"(c[1]), "=f"(c[2]), "=f"(c[3]) : "r"(a0), "r"(a1), "r"(a2), "r"(a3), "r"(b0), "r"(b1), "f"(0.f));
}
__device__ __forceinline__ void mma_bf8(float (&c)[4], uint32_t a0, uint32_t a1, uint32_t b0) {
    asm("mma.sync.aligned.m16n8k8.row.col.f32.bf16.bf16.f32 {%0,%1,%2,%3}, {%4,%5}, {%6}, {%0,%1,%2,%3};"
        : "+f"(c[0]), "+f"(c[1]), "+f"(c[2]), "+f"(c[3]) : "r"(a0), "r"(a1), "r"(b0));
}
__device__ __forceinline__ void mma_f16(float (&c)[4], uint32_t a0, uint32_t a1, uint32_t a2, uint32_t a3, uint32_t b0, uint32_t b1) {
    asm("mma.sync.aligned.m16n8k16.row.col.f32.f16.f16.f32 {%0,%1,%2,%3}, {%4,%5,%6,%7}, {%8,%9}, {%0,%1,%2,%3};"
        : "+f"(c[0]), "+f"(c[1]), "+f"(c[2]), "+f"(c[3]) : "r"(a0), "r"(a1), "r"(a2), "r"(a3), "r"(b0), "r"(b1));
}
__device__ __forceinline__ uint32_t lds16(uint32_t a) { uint32_t v; asm volatile("ld.shared.u16 %0, [%1];" : "=r"(v) : "r"(a)); return v; }
__device__ __forceinline__ uint32_t lds8(uint32_t a) { uint32_t v; asm volatile("ld.shared.u8 %0, [%1];" : "=r"(v) : "r"(a)); return v; }
__device__ __forceinline__ uint32_t lds32(uint32_t a) { uint32_t v; asm volatile("ld.shared.u32 %0, [%1];" : "=r"(v) : "r"(a)); return v; }
__device__ __forceinline__ uint32_t lds32v(uint32_t a) { uint32_t v; asm volatile("ld.volatile.shared.u32 %0, [%1];" : "=r"(v) : "r"(a)); return v; }
__device__ __forceinline__ uint2 lds64(uint32_t a) { uint2 v; asm volatile("ld.shared.v2.u32 {%0,%1}, [%2];" : "=r"(v.x), "=r"(v.y) : "r"(a)); return v; }
__device__ __forceinline__ uint4 lds128(uint32_t a) { uint4 v; asm volatile("ld.shared.v4.u32 {%0,%1,%2,%3}, [%4];" : "=r"(v.x), "=r"(v.y), "=r"(v.z), "=r"(v.w) : "r"(a)); return v; }
__device__ __forceinline__ void ldsm4(uint32_t (&r)[4], uint32_t a) {
    asm volatile("ldmatrix.sync.aligned.m8n8.x4.shared.b16 {%0,%1,%2,%3}, [%4];" : "=r"(r[0]), "=r"(r[1]), "=r"(r[2]), "=r"(r[3]) : "r"(a));
}
__device__ __forceinline__ void ldsm4t(uint32_t (&r)[4], uint32_t a) {
    asm volatile("ldmatrix.sync.aligned.m8n8.x4.trans.shared.b16 {%0,%1,%2,%3}, [%4];" : "=r"(r[0]), "=r"(r[1]), "=r"(r[2]), "=r"(r[3]) : "r"(a));
}
__device__ __forceinline__ void sts16(uint32_t a, uint32_t v) { asm volatile("st.shared.u16 [%0], %1;" :: "r"(a), "r"(v) : "memory"); }
__device__ __forceinline__ void sts32(uint32_t a, uint32_t v) { asm volatile("st.shared.u32 [%0], %1;" :: "r"(a), "r"(v) : "memory"); }
__device__ __forceinline__ void sts64(uint32_t a, uint32_t x, uint32_t y) { asm volatile("st.shared.v2.u32 [%0], {%1,%2};" :: "r"(a), "r"(x), "r"(y) : "memory"); }
__device__ __forceinline__ void sts128(uint32_t a, uint32_t x, uint32_t y, uint32_t z, uint32_t w) {
    asm volatile("st.shared.v4.u32 [%0], {%1,%2,%3,%4};" :: "r"(a), "r"(x), "r"(y), "r"(z), "r"(w) : "memory");
}
__device__ __forceinline__ void stsm2(uint32_t a, uint32_t x, uint32_t y) {
    asm volatile("stmatrix.sync.aligned.m8n8.x2.shared.b16 [%0], {%1,%2};" :: "r"(a), "r"(x), "r"(y) : "memory");
}
__device__ __forceinline__ void stsm4t(uint32_t a, uint32_t r0, uint32_t r1, uint32_t r2, uint32_t r3) {
    asm volatile("stmatrix.sync.aligned.m8n8.x4.trans.shared.b16 [%0], {%1,%2,%3,%4};" :: "r"(a), "r"(r0), "r"(r1), "r"(r2), "r"(r3) : "memory");
}
__device__ __forceinline__ void st_async64(uint32_t a, uint32_t x, uint32_t y, uint32_t bar) {
    asm volatile("st.async.weak.shared::cluster.mbarrier::complete_tx::bytes.v2.b32 [%0], {%1,%2}, [%3];" :: "r"(a), "r"(x), "r"(y), "r"(bar) : "memory");
}
__device__ __forceinline__ void st_async128(uint32_t a, uint32_t x, uint32_t y, uint32_t z, uint32_t w, uint32_t bar) {
    asm volatile("st.async.weak.shared::cluster.mbarrier::complete_tx::bytes.v4.b32 [%0], {%1,%2,%3,%4}, [%5];" :: "r"(a), "r"(x), "r"(y), "r"(z), "r"(w), "r"(bar) : "memory");
}
__device__ __forceinline__ void mbar_init(uint32_t b, uint32_t cnt) { asm volatile("mbarrier.init.shared::cta.b64 [%0], %1;" :: "r"(b), "r"(cnt) : "memory"); }
__device__ __forceinline__ void mbar_fence_init() { asm volatile("fence.mbarrier_init.release.cluster;" ::: "memory"); }
__device__ __forceinline__ void mbar_expect(uint32_t b, uint32_t bytes) { asm volatile("mbarrier.arrive.expect_tx.shared::cta.b64 _, [%0], %1;" :: "r"(b), "r"(bytes) : "memory"); }
__device__ __forceinline__ void mbar_arrive(uint32_t b) { asm volatile("mbarrier.arrive.shared::cta.b64 _, [%0];" :: "r"(b) : "memory"); }
__device__ __forceinline__ void mbar_wait(uint32_t b) {
    asm volatile("{ .reg .pred p; .reg .u32 n; mov.u32 n, 0;\n"
                 "W: mbarrier.try_wait.parity.shared::cta.b64 p, [%0], 0; @p bra D; add.u32 n, n, 1; setp.lt.u32 p, n, 4000000; @p bra W; trap;\n"
                 "D: }" :: "r"(b) : "memory");
}
__device__ __forceinline__ bool mbar_test(uint32_t b) {
    uint32_t d; asm volatile("{ .reg .pred p; mbarrier.test_wait.parity.shared::cta.b64 p, [%1], 0; selp.u32 %0, 1, 0, p; }" : "=r"(d) : "r"(b) : "memory"); return d;
}
__device__ __forceinline__ void tma2d(uint32_t dst, const CUtensorMap* m, int c0, int c1, uint32_t bar) {
    asm volatile("cp.async.bulk.tensor.2d.shared::cluster.global.mbarrier::complete_tx::bytes [%0], [%1, {%3, %4}], [%2];"
                 :: "r"(dst), "l"(m), "r"(bar), "r"(c0), "r"(c1) : "memory");
}
__device__ __forceinline__ void tma5d(uint32_t dst, const CUtensorMap* m, int c0, int c1, int c2, int c3, int c4, uint32_t bar) {
    asm volatile("cp.async.bulk.tensor.5d.shared::cluster.global.mbarrier::complete_tx::bytes [%0], [%1, {%3, %4, %5, %6, %7}], [%2];"
                 :: "r"(dst), "l"(m), "r"(bar), "r"(c0), "r"(c1), "r"(c2), "r"(c3), "r"(c4) : "memory");
}
__device__ __forceinline__ uint32_t mapa(uint32_t a, uint32_t rank) { uint32_t r; asm("mapa.shared::cluster.u32 %0, %1, %2;" : "=r"(r) : "r"(a), "r"(rank)); return r; }
__device__ __forceinline__ void prefetch_map(const CUtensorMap* m) { asm volatile("prefetch.tensormap [%0];" :: "l"(m) : "memory"); }
__device__ __forceinline__ void bar_sync(int id, int n) { asm volatile("bar.sync %0, %1;" :: "r"(id), "r"(n) : "memory"); }
__device__ __forceinline__ void bar_arrive(int id, int n) { asm volatile("bar.arrive %0, %1;" :: "r"(id), "r"(n) : "memory"); }
__device__ __forceinline__ void cluster_arrive_relaxed() { asm volatile("barrier.cluster.arrive.relaxed.aligned;" ::: "memory"); }
__device__ __forceinline__ void cluster_wait() { asm volatile("barrier.cluster.wait.aligned;" ::: "memory"); }
__device__ __forceinline__ uint32_t ld_rlx32(const void* p) { uint32_t v; asm volatile("ld.relaxed.gpu.global.u32 %0, [%1];" : "=r"(v) : "l"(p) : "memory"); return v; }
__device__ __forceinline__ uint4 ld_rlx128(const void* p) {
    uint4 v; asm volatile("ld.relaxed.gpu.global.v4.u32 {%0,%1,%2,%3}, [%4];" : "=r"(v.x), "=r"(v.y), "=r"(v.z), "=r"(v.w) : "l"(p) : "memory"); return v;
}
__device__ __forceinline__ uint32_t take_ticket(unsigned* p) { uint32_t v; asm volatile("atom.relaxed.gpu.global.add.u32 %0, [%1], 1;" : "=r"(v) : "l"(p) : "memory"); return v; }
__device__ __forceinline__ void st_rlx32(void* p, uint32_t v) { asm volatile("st.relaxed.gpu.global.u32 [%0], %1;" :: "l"(p), "r"(v) : "memory"); }
__device__ __forceinline__ void st_pkt(void* p, uint32_t x, uint32_t y, uint32_t z, uint32_t w) {
    asm volatile("{ .reg .b64 lo, hi; .reg .b128 v; mov.b64 lo, {%1, %2}; mov.b64 hi, {%3, %4}; mov.b128 v, {lo, hi}; st.relaxed.gpu.global.b128 [%0], v; }"
                 :: "l"(p), "r"(x), "r"(y), "r"(z), "r"(w) : "memory");
}
__device__ __forceinline__ uint4 ld_pkt(const void* p) {
    uint4 r;
    asm volatile("{ .reg .b64 lo, hi; .reg .b128 v; ld.relaxed.gpu.global.b128 v, [%4]; mov.b128 {lo, hi}, v; mov.b64 {%0, %1}, lo; mov.b64 {%2, %3}, hi; }"
                 : "=r"(r.x), "=r"(r.y), "=r"(r.z), "=r"(r.w) : "l"(p) : "memory");
    return r;
}
__device__ __forceinline__ uint32_t tag_of(uint32_t ticket) { return ticket / NCTA % 3u + 1u; }
__device__ __forceinline__ uint2 ldg64(const void* p) { uint2 v; asm volatile("ld.global.nc.v2.u32 {%0,%1}, [%2];" : "=r"(v.x), "=r"(v.y) : "l"(p)); return v; }
__device__ __forceinline__ uint4 ldg128(const void* p) { uint4 v; asm volatile("ld.global.nc.v4.u32 {%0,%1,%2,%3}, [%4];" : "=r"(v.x), "=r"(v.y), "=r"(v.z), "=r"(v.w) : "l"(p)); return v; }
__device__ __forceinline__ uint32_t ldg32(const void* p) { uint32_t v; asm volatile("ld.global.nc.u32 %0, [%1];" : "=r"(v) : "l"(p)); return v; }
__device__ __forceinline__ uint32_t ldg16(const void* p) { uint32_t v; asm volatile("ld.global.nc.u16 %0, [%1];" : "=r"(v) : "l"(p)); return v; }
__device__ __forceinline__ int warp_id() { return __shfl_sync(0xffffffffu, threadIdx.x >> 5, 0); }
__device__ __forceinline__ uint32_t clk() { uint32_t t; asm volatile("mov.u32 %0, %clock;" : "=r"(t) :: "memory"); return t; }
__device__ __forceinline__ void spin_until(uint32_t t0, uint32_t d) { while (clk() - t0 < d) { SPIN; } }
__device__ __forceinline__ float sigmoidf_(float x) { return __fdividef(1.0f, 1.0f + __expf(-x)); }
__device__ __forceinline__ int key_row(uint32_t key) { return 2047 - (int)(key & 2047u); }
__device__ __forceinline__ float key_val(uint32_t key) {
    const uint32_t o = key & 0xffff0000u; return __uint_as_float((o & 0x80000000u) ? (o & 0x7fffffffu) : (~o & 0xffff0000u));
}
#define POLL_GUARD(it) if (++(it) > (1 << 20)) __trap()

constexpr int UT_PL = 2240, UT_STRIDE = 4544;
constexpr int KT_P = 0, KT_P4 = 544 * 4, KT_P8 = KT_P4 + 172 * 4, KT_BYTES = KT_P8 + 140 * 4;
constexpr int KG_ROW = 272, KG_STAGE = 33 * KG_ROW;
constexpr int OUT_HALF = 2368, OUT_STAGE = 2 * OUT_HALF;
constexpr int SC_UTILE = 0;
constexpr int SC_UT = 32768;
constexpr int SC_STG = SC_UT + 8 * UT_STRIDE;
constexpr int SC_KT = SC_STG + 8 * KG_STAGE;
constexpr int SC_OUT = SC_KT + 8 * KT_BYTES;
constexpr int SC_RED = SC_OUT + 8 * OUT_STAGE;
constexpr int SC_CT = SC_RED + 2048;
constexpr int SC_BAR = SC_CT + 2560;
constexpr int SB_UT = SC_BAR + 32, SB_PRE = SC_BAR + 48, SB_OUT = SC_BAR + 64, SC_KEY = SC_BAR + 128, SC_TAG = SC_BAR + 160;
constexpr int SC_END = SC_BAR + 256;
static_assert(SC_STG % 128 == 0 && SC_OUT % 128 == 0 && SC_KT % 16 == 0, "align");
constexpr int PIECE = 20480;
constexpr int SF_R = 9 * PIECE;
constexpr int SF_XS = SF_R + 36864;
constexpr int SF_STG = 4 * PIECE, SF_R4 = 8 * PIECE + 8192;
constexpr int SF_LIST = SF_XS, SF_WR = SF_XS + 4096;
constexpr int SF_H = SF_XS + 9344;
constexpr int SF_BAR = SF_H + 1280;
constexpr int SF_MAX = SF_BAR + 208, SF_CNT = SF_MAX + 64, SF_TK = SF_CNT + 4, SF_CLK = SF_CNT + 8, SF_SEL = SF_CNT + 16;
constexpr int SF_END = SF_SEL + 32;
constexpr int SM_TIM = SF_END;
constexpr int SMEM_BYTES = SF_END + 256;
static_assert(SF_STG + 10 * KG_STAGE <= SF_R4 && SMEM_BYTES <= 232448 && SC_END <= SF_END, "smem");

struct cplx { float re, im; };
struct h2c { uint32_t re, im; };
__device__ __forceinline__ cplx csq(cplx a) {
    cplx r; r.re = a.re * a.re - a.im * a.im;
    asm("{ .reg .f32 t; mul.f32 t, %1, %2; mul.f32 %0, t, 0f40000000; }" : "=f"(r.im) : "f"(a.re), "f"(a.im));
    return r;
}
__device__ __forceinline__ float ex2(float x) { float m; asm("ex2.approx.ftz.f32 %0, %1;" : "=f"(m) : "f"(x)); return m; }
__device__ __forceinline__ cplx cexp2(float x, float y) {
    const float m = ex2(x);
    cplx o; o.re = m * __cosf(y); o.im = m * __sinf(y); return o;
}
__device__ __forceinline__ h2c hpack(cplx a, cplx b) { h2c r; r.re = pack_f16(a.re, b.re); r.im = pack_f16(a.im, b.im); return r; }
__device__ __forceinline__ h2c hmulc(h2c a, h2c m) {
    h2c r;
    asm("{ .reg .b32 s, t; mul.f16x2 s, %3, %5; mul.f16x2 t, %3, %4; neg.f16x2 s, s; fma.rn.f16x2 %0, %2, %4, s; fma.rn.f16x2 %1, %2, %5, t; }"
        : "=&r"(r.re), "=r"(r.im) : "r"(a.re), "r"(a.im), "r"(m.re), "r"(m.im));
    return r;
}
__device__ __forceinline__ h2c hmulj(h2c a, h2c m) {
    h2c r;
    asm("{ .reg .b32 s, t; mul.f16x2 s, %3, %5; mul.f16x2 t, %2, %5; neg.f16x2 t, t; fma.rn.f16x2 %0, %2, %4, s; fma.rn.f16x2 %1, %3, %4, t; }"
        : "=&r"(r.re), "=r"(r.im) : "r"(a.re), "r"(a.im), "r"(m.re), "r"(m.im));
    return r;
}

struct KParams { uint32_t v[6], logdt, dskip; };
__device__ __forceinline__ KParams kload(const Params& p, int ch, int half) {
    KParams k;
    const int o = ch * NST + 64 * half + 2 * (threadIdx.x & 31);
    const __nv_bfloat16* a[8] = {p.Are + o, p.Aim + o, p.Bre + o, p.Bim + o, p.Cre + o, p.Cim + o, p.logdt + ch, p.Dskip + ch};
#pragma unroll
    for (int i = 0; i < 6; i++) k.v[i] = ldg32(a[i]);
    k.logdt = ldg16(a[6]); k.dskip = ldg16(a[7]);
    return k;
}

__device__ __forceinline__ void kgen(const KParams& k, uint32_t stage, float (&kv)[21], float& fin, uint32_t sb) {
    const int lane = threadIdx.x & 31, mi = lane >> 3, r8 = lane & 7;
    const uint32_t (&v)[6] = k.v;
    const uint32_t w2 = stage + (lane & 15) * 16, w1 = stage + lane * 4;
    auto put = [&](int row, h2c x) { stsm2(w2 + row * KG_ROW, x.re, x.im); };
    auto keep = [&](int row, h2c x) { sts32(w1 + row * KG_ROW, x.re); sts32(w1 + row * KG_ROW + 128, x.im); };
    sts32(w1, 0x3c003c00u); sts32(w1 + 128, 0u);
    const float dt = rbf(ex2(bf_lo(k.logdt) * 1.4426950408889634f));
    const float dl = dt * 1.4426950408889634f;
    const float xa = bf_lo(v[0]) * dl, xb = bf_hi(v[0]) * dl, ya = bf_lo(v[1]) * dt, yb = bf_hi(v[1]) * dt;
    cplx a = cexp2(xa, ya), b = cexp2(xb, yb), c = cexp2(64.f * xa, 64.f * ya), d = cexp2(64.f * xb, 64.f * yb);
    cplx Wa, Wb;
    Wa.re = bf_lo(v[4]) * bf_lo(v[2]) - bf_lo(v[5]) * bf_lo(v[3]); Wa.im = bf_lo(v[4]) * bf_lo(v[3]) + bf_lo(v[5]) * bf_lo(v[2]);
    Wb.re = bf_hi(v[4]) * bf_hi(v[2]) - bf_hi(v[5]) * bf_hi(v[3]); Wb.im = bf_hi(v[4]) * bf_hi(v[3]) + bf_hi(v[5]) * bf_hi(v[2]);
    const float mx = fmaxf(fmaxf(fabsf(Wa.re), fabsf(Wa.im)), fmaxf(fabsf(Wb.re), fabsf(Wb.im)));
    const uint32_t ex = max(__reduce_max_sync(0xffffffffu, __float_as_uint(mx)) >> 23, 10u);
    const float sc = __uint_as_float((263u - ex) << 23);
    fin = dt * __uint_as_float((ex - 9u) << 23);
    Wa.re *= sc; Wa.im *= sc; Wb.re *= sc; Wb.im *= sc;
    kv[16] = (float)__reduce_add_sync(0xffffffffu, __float2int_rn((Wa.re + Wb.re) * 32768.f)) * (1.f / 32768.f);
    h2c c1;
    {
        cplx p, q;
        p.re = Wa.re * a.re - Wa.im * a.im; p.im = -(Wa.re * a.im) - Wa.im * a.re; q.re = Wb.re * b.re - Wb.im * b.im; q.im = -(Wb.re * b.im) - Wb.im * b.re;
        c1 = hpack(p, q);
    }
    const h2c z1 = hpack(a, b); a = csq(a); b = csq(b);
    const h2c z64 = hpack(c, d); c = csq(c); d = csq(d);
    const h2c z2 = hpack(a, b); a = csq(a); b = csq(b);
    const h2c z128 = hpack(c, d); c = csq(c); d = csq(d);
    const h2c z4 = hpack(a, b); a = csq(a); b = csq(b);
    const h2c z256 = hpack(c, d); c = csq(c); d = csq(d);
    const h2c z8 = hpack(a, b); a = csq(a); b = csq(b);
    const h2c z512 = hpack(c, d);
    const h2c z16 = hpack(a, b); a = csq(a); b = csq(b);
    const h2c z32 = hpack(a, b);
    keep(32, z64);
    const h2c c2 = hmulj(c1, z1), c3 = hmulj(c1, z2), c4 = hmulj(c2, z2), c6 = hmulj(c2, z4), c8 = hmulj(c4, z4);
    keep(8, c1); keep(9, c2); keep(10, c3); keep(11, c4); put(12, hmulj(c1, z4)); keep(13, c6); put(14, hmulj(c3, z4)); keep(15, c8);
    const h2c e260 = hmulj(c4, z256), e264 = hmulj(c8, z256), e776 = hmulj(e264, z512), e840 = hmulj(e776, z64);
    put(16, hmulj(c2, z256)); put(17, hmulj(c4, z512)); keep(18, e260); put(19, hmulj(c8, z512)); put(20, hmulj(c6, z256)); put(21, hmulj(e260, z512)); keep(22, e264); keep(23, e776);
    const h2c z24 = hmulc(z8, z16);
    keep(1, z8); keep(2, z16); keep(3, z24); keep(4, z32); put(5, hmulc(z8, z32)); put(6, hmulc(z16, z32)); put(7, hmulc(z24, z32));
    const h2c d0 = hmulj(e840, z128), d1 = hmulj(e840, z256), d3 = hmulj(e840, z512), d2 = hmulj(d0, z256);
    keep(24, d0); keep(25, d1); keep(27, d3); keep(26, d2); put(28, hmulj(d0, z512)); put(29, hmulj(d1, z512)); put(31, hmulj(d3, z512)); put(30, hmulj(d2, z512));
    __syncwarp();
    const uint32_t ra = stage + ((mi & 1) ? 32 : r8) * KG_ROW + (mi >> 1) * 128, rb = stage + (8 + r8) * KG_ROW + (mi & 1) * 128 + (mi >> 1) * 16;
    float acc[5][4];
#pragma unroll
    for (int i = 0; i < 5; i++) acc[i][0] = acc[i][1] = acc[i][2] = acc[i][3] = 0.f;
#pragma unroll
    for (int s = 0; s < 4; s++) {
        uint32_t A[2][4], B[3][4];
        ldsm4(A[0], ra + 32 * s); ldsm4(A[1], ra + 32 * s + 16);
        ldsm4(B[0], rb + 32 * s); ldsm4(B[1], rb + 32 * s + 8 * KG_ROW); ldsm4(B[2], rb + 32 * s + 16 * KG_ROW);
#pragma unroll
        for (int e = 0; e < 2; e++) {
            const h2c p0 = {A[e][0], A[e][2]}, m = {A[e][1], A[e][3]};
            const h2c p1 = hmulc(p0, m), p2 = hmulc(p1, m), p3 = hmulc(p2, m);
            mma_f16(acc[1], p1.re, p2.re, p1.im, p2.im, B[0][2 * e], B[0][2 * e + 1]);
            mma_f16(acc[3], p1.re, p2.re, p1.im, p2.im, B[1][2 * e], B[1][2 * e + 1]);
            mma_f16(acc[4], p1.re, p2.re, p1.im, p2.im, B[2][2 * e], B[2][2 * e + 1]);
            mma_f16(acc[0], p0.re, p3.re, p0.im, p3.im, B[0][2 * e], B[0][2 * e + 1]);
            mma_f16(acc[2], p0.re, p3.re, p0.im, p3.im, B[1][2 * e], B[1][2 * e + 1]);
        }
    }
#pragma unroll
    for (int q = 0; q < 4; q++) {
        const int i = (q == 1 || q == 2), h = 2 * (q >> 1);
        kv[2 * q] = acc[i][h]; kv[2 * q + 1] = acc[i][h + 1]; kv[8 + q] = acc[2 + i][h]; kv[12 + q] = acc[2 + i][h + 1]; kv[17 + q] = acc[4][2 * (q & 1) + (q >> 1)];
    }
}
__device__ __forceinline__ void kswap(float (&kv)[21], float fin, uint32_t mine, uint32_t other, bool second, int bar, uint32_t dskip) {
    const uint32_t lo = (threadIdx.x & 31) * 16;
    auto send = [&](int i, int k) { sts128(mine + lo + 512 * i, __float_as_uint(kv[k] * fin), __float_as_uint(kv[k + 1] * fin), __float_as_uint(kv[k + 2] * fin), __float_as_uint(kv[k + 3] * fin)); };
    auto recv = [&](int i, int k) {
        const uint4 x = lds128(other + lo + 512 * i);
        kv[k] = kv[k] * fin + __uint_as_float(x.x); kv[k + 1] = kv[k + 1] * fin + __uint_as_float(x.y); kv[k + 2] = kv[k + 2] * fin + __uint_as_float(x.z); kv[k + 3] = kv[k + 3] * fin + __uint_as_float(x.w);
    };
    __syncwarp();
    if (second) {
        send(0, 17);
        bar_sync(bar, 64);
        recv(0, 0); recv(1, 4); recv(2, 8); recv(3, 12);
        kv[16] = kv[16] * fin + __uint_as_float(lds32(other + 2048)) + bf_lo(dskip);
    } else {
        send(0, 0); send(1, 4); send(2, 8); send(3, 12);
        sts32(mine + 2048, __float_as_uint(kv[16] * fin));
        bar_sync(bar, 64);
        recv(0, 17);
    }
}

__device__ __forceinline__ void ktables(float (&kv)[21], uint32_t kt) {
    const int lane = threadIdx.x & 31, g = lane >> 2, t = lane & 3;
    const float k512 = rbf(__shfl_sync(0xffffffffu, kv[11], 31));
    if (lane >= 30) kv[11] = lane == 31 ? 0.f : kv[11] - k512;
    float carry = kv[16];
    if (lane == 0) sts32(kt + KT_P + 15 * 4, pack_bf16(carry, 0.f));
#pragma unroll
    for (int q = 0; q < 8; q++) {
        const float hi = q < 4 ? kv[2 * q + 1] : kv[4 + q];
        const float sh = __shfl_sync(0xffffffffu, hi, (lane + 31) & 31);
        const float prev = lane ? sh : carry;
        carry = sh;
        const float lo = q < 4 ? kv[2 * q] : ((lane & 1) ? hi : prev);
        sts64(kt + KT_P + (64 * q + 16) * 4 + lane * 8, pack_bf16(lo, prev), pack_bf16(hi, lo));
    }
    const uint32_t a4 = kt + KT_P4 + (13 + 2 * g + (t & 1) + 64 * (t >> 1)) * 4;
    const float up = __shfl_up_sync(0xffffffffu, kv[15], 2);
    sts32(a4, pack_bf16(kv[12], t >= 2 ? up : lane == 29 ? k512 : 0.f));
#pragma unroll
    for (int q = 1; q < 4; q++) sts32(a4 + 64 * q, pack_bf16(kv[12 + q], kv[11 + q]));
    sts32(t >= 2 ? a4 + 256 : kt + KT_P4 + 12 * 4, t >= 2 ? pack_bf16(0.f, kv[15]) : pack_bf16(k512, 0.f));
}
__device__ __forceinline__ void ktable8(const float (&kv)[21], uint32_t kt) {
    const int lane = threadIdx.x & 31, g = lane >> 2, t = lane & 3;
    const uint32_t a8 = kt + KT_P8 + (6 + 32 * t + g) * 4;
    const float up = __shfl_up_sync(0xffffffffu, kv[20], 1);
#pragma unroll
    for (int q = 1; q < 4; q++) sts32(a8 + 32 * q, pack_bf16(kv[17 + q], kv[16 + q]));
    sts32(a8, pack_bf16(kv[17], t ? up : 0.f));
    __syncwarp();
}

__device__ __forceinline__ uint32_t band(int e, int c, int h) {
    return (((unsigned)(e - c + h) <= 2u * h) ? 0x3f80u : 0u) | (((unsigned)(e + 1 - c + h) <= 2u * h) ? 0x3f800000u : 0u);
}

__device__ __forceinline__ void conv_consts(uint32_t sb, int rank) {
    const int lane = threadIdx.x & 31, g = lane >> 2, t = lane & 3, mi = lane >> 3, r8 = lane & 7, d0 = g - 2 * t, pg = (g >> 1) + 4 * (g & 1);
    const uint32_t a = sb + SC_CT + lane * 16;
    sts128(a, band(4 * t, 4 + g, 4), band(4 * t, 4 + g, 3), band(4 * t + 2, 4 + g, 4), band(4 * t + 2, 4 + g, 3));
    sts128(a + 512, pg * 16 + (t == 0 ? UT_PL - 8 : t == 3 ? UT_PL : 8 * (t - 1)), pg * 16 + (t == 0 ? -8 : t == 3 ? 0 : UT_PL - 16 + 8 * (t - 1)),
           (mi & 1) * UT_PL + (mi >> 1) * 128 + r8 * 16, KT_P + (15 + d0) * 4);
    sts128(a + 1024, (((unsigned)(d0 - 3) < 2u) ? 0xffffu : 0u) | (((unsigned)(d0 - 4) < 2u) ? 0xffff0000u : 0u),
           (((unsigned)(d0 + 5) < 2u) ? 0xffffu : 0u) | (((unsigned)(d0 + 4) < 2u) ? 0xffff0000u : 0u), KT_P4 + (3 + g - t) * 16, UT_PL - 16 + lane * 16);
    sts128(a + 1536, band(2 * t, 6 + g, 2), band(2 * t, 2 + g, 1), band(2 * t + 8, 6 + g, 2), band(2 * t + 8, 2 + g, 1));
    sts128(a + 2048, pg * 16 + (t == 3 ? UT_PL : 4 + 4 * t), pg * 16 + (t == 3 ? 16 : UT_PL + 4 + 4 * t),
           mapa(sb + SC_OUT + rank * OUT_HALF + g * 32 + (t & 1) * 16, t >> 1), mapa(sb + SB_OUT, t >> 1));
}

__device__ __forceinline__ void conv_warp(uint32_t sb, int warp) {
    const int lane = threadIdx.x & 31;
    const uint32_t kt = sb + SC_KT + warp * KT_BYTES, ut = sb + SC_UT + warp * UT_STRIDE + 128, ct = sb + SC_CT + lane * 16;
    float acc[16][4];
    const uint32_t oz = blockIdx.y;
    const uint4 c1 = lds128(ct + 512);
    {
        uint32_t kb[8][2];
#pragma unroll
        for (int l = 0; l < 8; l++) { const uint2 x = lds64(kt + KT_P8 + (3 + 8 * l + (lane >> 2) - (lane & 3)) * 8); kb[l][0] = x.x; kb[l][1] = x.y; }
        const uint4 c0 = lds128(ct);
        const uint32_t w0 = c0.x, w1 = c0.y, w2 = c0.z, w3 = c0.w, a0 = ut + c1.x, a1 = ut + c1.y;
        mbar_wait(sb + SB_UT);
#pragma unroll
        for (int j = 0; j < 8; j++) {
            const uint2 x = lds64(a0 + 128 * j - 16), y = lds64(a1 + 128 * j), z = lds64(a0 + 128 * j);
            float X[4], Y[4], Z[4];
            mma_bf0(X, w0, w1, w2, w3, x.x, x.y); mma_bf0(Y, w0, w1, w2, w3, y.x, y.y); mma_bf0(Z, w0, w1, w2, w3, z.x, z.y);
            const uint32_t q0 = pack_bf16(Y[2], Y[3]), q1 = pack_bf16(Z[2], Z[3]), q2 = pack_bf16(X[0], X[1]), q3 = pack_bf16(Y[0], Y[1]);
#pragma unroll
            for (int l = 0; l < 8 - j; l++) {
                if (j == 0) mma_bf0(acc[8 + l], q0, q1, q2, q3, kb[l][0], kb[l][1]);
                else mma_bf(acc[8 + j + l], q0, q1, q2, q3, kb[l][0], kb[l][1]);
            }
        }
    }
    if (warp < 4) { bar_sync(6 + warp, 64); mbar_wait(sb + SB_UT + 8); }
    uint4 c2;
    {
        uint32_t a[4][4], b[8][4];
        uint32_t k1 = kt + c1.w, u1 = ut + c1.z;
        auto lda = [&](int j1) { a[j1][0] = lds32(k1 + 512 * j1); a[j1][1] = lds32(k1 + 512 * j1 + 32); a[j1][2] = lds32v(k1 + 512 * j1 - 32); a[j1][3] = DUPA; };
        lda(0);
#pragma unroll
        for (int m2 = 0; m2 < 8; m2++) ldsm4(b[m2], u1 + 256 * m2);
#pragma unroll
        for (int i = 0; i < 8; i++) acc[i][0] = acc[i][1] = acc[i][2] = acc[i][3] = 0.f;
#pragma unroll DUNR
        for (int j0 = 0; j0 < 8; j0++) {
            k1 += 64; u1 -= 16;
            lda(3);
#pragma unroll
            for (int m = 0; m < 16; m++) {
                mma_bf(acc[m], a[0][0], a[0][1], a[0][2], a[0][3], b[m >> 1][2 * (m & 1)], b[m >> 1][2 * (m & 1) + 1]);
                if (m & 1) ldsm4(b[m >> 1], u1 + 256 * (m >> 1));
            }
            lda(2); lda(1); lda(0);
#pragma unroll
            for (int j1 = 3; j1 > 0; j1--)
#pragma unroll
                for (int m = 0; m + j1 < 16; m++) mma_bf(acc[m + j1], a[j1][0], a[j1][1], a[j1][2], a[j1][3], b[m >> 1][2 * (m & 1)], b[m >> 1][2 * (m & 1) + 1]);
        }
        c2 = lds128(ct + 1024);
        const uint32_t kv = __byte_perm(lds32(kt + KT_P4 + 140 * 4), 0, 0x1010), e0 = kv & c2.x, e1 = kv & c2.y;
        const uint32_t e3 = e0 + oz, e4 = e1 + oz, z2 = oz + oz;
        uint32_t f[2][4];
        ldsm4(f[0], ut + c2.w); ldsm4(f[1], ut + c2.w + 512);
#pragma unroll
        for (int m = 1; m < 16; m++) mma_bf(acc[m], a[0][0], a[0][1], a[0][2], a[0][3], b[m >> 1][2 * (m & 1)], b[m >> 1][2 * (m & 1) + 1]);
#pragma unroll
        for (int m = 1; m < 9; m++) mma_bf(acc[m + 7], e0, e1, oz, e3, b[m >> 1][2 * (m & 1)], b[m >> 1][2 * (m & 1) + 1]);
#pragma unroll
        for (int m = 0; m < 8; m++) mma_bf8(acc[m + 8], e4, z2, f[m >> 2][m & 3]);
    }
    uint32_t kb[5][4];
#pragma unroll
    for (int l = 0; l < 5; l++) { const uint4 x = lds128(kt + c2.z + 128 * l); kb[l][0] = x.x; kb[l][1] = x.y; kb[l][2] = x.z; kb[l][3] = x.w; }
    const uint4 c3 = lds128(ct + 1536), c4 = lds128(ct + 2048);
    const uint32_t w0 = c3.x, w1 = c3.y, w2 = c3.z, w3 = c3.w, a0 = ut + c4.x, a1 = ut + c4.y, od = c4.z + warp * 288, ob = c4.w;
    auto emit = [&](int q) {
        st_async128(od + q * OUT_STAGE, pack_bf16(acc[2 * q][0], acc[2 * q][1]), pack_bf16(acc[2 * q][2], acc[2 * q][3]),
                    pack_bf16(acc[2 * q + 1][0], acc[2 * q + 1][1]), pack_bf16(acc[2 * q + 1][2], acc[2 * q + 1][3]), ob + 8 * q);
    };
    uint32_t x[12][4];
    auto load = [&](int j) { x[j][0] = lds32(a0 + 128 * j - 16); x[j][1] = lds32(a1 + 128 * j - 16); x[j][2] = lds32(a0 + 128 * j); x[j][3] = lds32(a1 + 128 * j); };
    load(0); load(1);
    emit(0); emit(1);
#pragma unroll
    for (int j = 0; j < 12; j++) {
        if (j == JBAR) bar_sync(11 + (warp & 3), 64);
        if (j + 2 < 11) load(j + 2);
        if (j == 10) load(11);
        float X[4], Y[4], Z[4];
        mma_bf0(X, w0, w1, w2, w3, x[j][0], x[j][1]); mma_bf0(Y, w0, w1, w2, w3, x[j][1] + oz, x[j][2] + oz); mma_bf0(Z, w0, w1, w2, w3, x[j][2], x[j][3]);
        const uint32_t x5 = pack_bf16(X[0], X[1]), x3 = pack_bf16(X[2], X[3]), y5 = pack_bf16(Y[0], Y[1]), y3 = pack_bf16(Y[2], Y[3]), z5 = pack_bf16(Z[0], Z[1]), z3 = pack_bf16(Z[2], Z[3]);
        const uint32_t y3c = y3 + oz, y5c = y5 + oz;
#pragma unroll
        for (int l = 0; l < 5; l++) if (j + 4 + l < 16) mma_bf(acc[j + 4 + l], y5, z5, y3, z3, kb[l][0], kb[l][1]);
#pragma unroll
        for (int l = 0; l < 5; l++) if (j + 4 + l < 16) mma_bf(acc[j + 4 + l], x5, y5c, x3, y3c, kb[l][2], kb[l][3]);
        if (j & 1) emit(2 + (j >> 1));
    }
}

__device__ __forceinline__ uint32_t utile_addr(uint32_t sb, int row, int c8) {
    return sb + SC_UTILE + (row >> 9) * 8192 + (((row >> 4) & 3) + 4 * (row & 1) + 8 * ((row >> 7) & 3) + 32 * ((row >> 1) & 7)) * 32 + ((c8 ^ row) & 1) * 16;
}

__device__ __forceinline__ void conv_helper(const Params& p, const CUtensorMap* mU, uint32_t sb, int cb, int hw, uint32_t t0) {
    const int lane = threadIdx.x & 31, g = lane >> 2, t = lane & 3, mi = lane >> 3, r8 = lane & 7;
    const int rank = cb & 1, slab = cb >> 1;
    const uint32_t bar_out = sb + SB_OUT, s_key = sb + SC_KEY;
    asm volatile("setmaxnreg.dec.sync.aligned.u32 88;");
    uint32_t tag = 0;
    if (lane == 0) {
        const uint32_t b = sb + SC_BAR + 8 * hw;
        mbar_init(b, hw < 4 ? 1 : hw < 6 ? 9 : 8); mbar_init(bar_out + 8 * hw, 1);
        mbar_fence_init();
        if (hw < 6) mbar_expect(b, 8192);
        if (hw < 4) {
            spin_until(t0, hw < 2 ? UDELAY : VDELAY);
            tma5d(sb + SC_UTILE + hw * 8192, mU, 16 * slab, 4 * rank, 0, 4 * hw, 0, b);
        }
        mbar_expect(bar_out + 8 * hw, 4096);
        if (hw == 4) tag = take_ticket(&p.scr->launch);
    }
    __syncwarp();
    cluster_arrive_relaxed();
    if (lane < 16) sts128(sb + SC_UT + hw * UT_STRIDE + mi * UT_PL + r8 * 16, 0, 0, 0, 0);
    if (lane < 17) sts128(sb + SC_KT + hw * KT_BYTES + 16 * (lane < 4 ? lane : lane < 11 ? 128 + lane : 164 + lane), 0, 0, 0, 0);
    if (hw == 7) conv_consts(sb, rank);
    if (hw == 4) { tag = tag_of(__shfl_sync(0xffffffffu, tag, 0)); sts32(sb + SC_TAG, tag); }
    cluster_wait();
    __syncwarp();
    if (lane == 0) mbar_arrive(sb + SB_PRE);
    {
        const int box = hw >> 2, h = hw & 1, k0 = hw & 2;
        const uint32_t src = sb + SC_UTILE + box * 8192 + h * 4096 + k0 * 256 + (32 * mi + (r8 >> 1) + 4 * (r8 & 1)) * 32;
        const uint32_t so = ((rank ^ r8) & 1) << 4;
        const uint32_t dst = sb + SC_UT + g * UT_STRIDE + 128 + h * UT_PL + k0 * 128 + (32 * box + 4 * rank + t) * 16;
        const uint32_t rdst = mapa(dst, rank ^ 1), rbar = mapa(sb + SB_UT, rank ^ 1);
#pragma unroll 1
        for (int i = 0; i < 2; i++) {
            mbar_wait(sb + SC_BAR + 8 * box + 16 * i);
            const uint32_t ts = clk();
            uint32_t a[2][4], b[2][4];
#pragma unroll
            for (int k = 0; k < 2; k++) { ldsm4t(a[k], src + (so ^ 16) + k * 256 + i * 16384); ldsm4t(b[k], src + so + k * 256 + i * 16384); }
#pragma unroll
            for (int k = 0; k < 2; k++) sts128(dst + k * 128 + i * 1024, b[k][0], b[k][1], b[k][2], b[k][3]);
#pragma unroll
            for (int k = 0; k < 2; k++) {
                if (k == 0) { __syncwarp(); if (lane == 0) mbar_arrive(sb + SB_UT + 8 * i); }
                spin_until(ts, (hw + 8 * k) * PACE);
                st_async128(rdst + k * 128 + i * 1024, a[k][0], a[k][1], a[k][2], a[k][3], rbar + 8 * i);
            }
        }
    }
    if (hw == 4) {
        uint32_t key;
        for (int it = 0;;) {
            key = ld_rlx32(&p.scr->sel[r8]);
            if (__all_sync(0xffffffffu, ((key >> 11) & 3u) == tag)) break;
            POLL_GUARD(it);
            __nanosleep(200);
        }
        if (lane < 8) sts32(s_key + 4 * lane, key);
    }
    bar_sync(1, 256);
    if (hw < 4) {
        const uint32_t last = lds32(s_key + 28), tg = ((last >> 11) & 3u) << 14;
        const int par = hw >> 1, i0 = 4 * (hw & 1);
        const int row0 = 256 * par + 128 * (g >> 2) + 64 * rank + 32 * (t >> 1) + 16 * (g & 1) + 8 * ((g >> 1) & 1) + i0;
        uint4 r[4];
        for (int it = 0;;) {
            uint32_t bad = 0;
#pragma unroll
            for (int k = 0; k < 4; k++) { r[k] = ld_rlx128(&p.scr->rec[row0 + 512 * k]); }
#pragma unroll
            for (int k = 0; k < 4; k++) bad |= (r[k].x ^ tg) | (r[k].y ^ tg) | (r[k].z ^ tg) | (r[k].w ^ tg);
            if ((bad & 0xc000u) == 0) break;
            POLL_GUARD(it);
        }
        const uint32_t thr = last & ~0x1800u;
        const uint32_t ya = sb + SC_OUT + par * OUT_STAGE + ((r8 >> 1) & 1) * OUT_HALF + (2 * mi + (r8 & 1)) * 288 + (2 * i0 + (r8 >> 2)) * 16;
        const uint32_t ua = utile_addr(sb, row0, t & 1);
        __nv_bfloat16* op = p.out + row0 * DM + 16 * slab + 8 * (t & 1);
#pragma unroll
        for (int k = 0; k < 4; k++) {
            const uint32_t rr[4] = {r[k].x, r[k].y, r[k].z, r[k].w};
            uint4 ou[4];
            uint32_t gg[4];
#pragma unroll
            for (int i = 0; i < 4; i++) {
                gg[i] = __byte_perm(rr[i], 0, 0x1010) & 0x3fff3fffu;
                const uint32_t om = hsub2(0x3f803f80u, gg[i]);
                const uint4 u4 = lds128((ua ^ ((i & 1) * 16)) + k * 8192 + (i & 1) * 128 + (i >> 1) * 1024);
                ou[i] = make_uint4(hmul2(om, u4.x), hmul2(om, u4.y), hmul2(om, u4.z), hmul2(om, u4.w));
            }
            mbar_wait(bar_out + 8 * par + 16 * k);
            uint32_t y[4][4];
#pragma unroll
            for (int i = 0; i < 4; i++) ldsm4t(y[i], ya + 2 * k * OUT_STAGE + 32 * i);
#pragma unroll
            for (int i = 0; i < 4; i++) {
                const uint4 o = make_uint4(hfma2(gg[i], y[i][0], ou[i].x), hfma2(gg[i], y[i][1], ou[i].y), hfma2(gg[i], y[i][2], ou[i].z), hfma2(gg[i], y[i][3], ou[i].w));
                if (((rr[i] & 0xffff0000u) | (uint32_t)(2047 - 512 * k - i - row0)) < thr) *(uint4*)(op + (512 * k + i) * DM) = o;
            }
        }
    } else {
        const int gw = hw - 4, ht = 32 * gw + lane, tok = ht >> 4, c = ht & 15;
        const uint32_t key = lds32(s_key + 4 * tok);
        tag = (key >> 11) & 3u;
        const int row = key_row(key);
        const bool own = ((row >> 6) & 1) == rank, take = ((key_row(lds32(s_key + 4 * g)) >> 6) & 1) == rank;
        if (!__any_sync(0xffffffffu, take)) return;
        uint32_t rc = 0;
        if (own) for (int it = 0;;) { rc = ld_rlx32(&p.scr->rec[row]); if (((rc >> 14) & 3u) == tag) break; POLL_GUARD(it); }
        const float gt = bf_lo(rc & 0x3fffu), om = rbf(1.f - gt), rs = rbf(sigmoidf_(key_val(key)));
        const float xv = bf_lo(lds16((utile_addr(sb, row, c >> 3)) + (c & 7) * 2));
        const uint4* src = p.scr->part + (slab * NFFN + 15 * gw) * 32;
        for (int it = 0;;) {
            const uint32_t w = ld_rlx32(src + min(lane, 14) * 32);
            if (__any_sync(0xffffffffu, (w & 3u) == tag)) break;
            POLL_GUARD(it);
            __nanosleep(100);
        }
        uint4 v[15];
#pragma unroll
        for (int k = 0; k < 15; k++) v[k] = make_uint4(take ? 0u : tag, 0u, 0u, 0u);
        for (int it = 0;;) {
#pragma unroll
            for (int k = 0; k < 15; k++) if ((v[k].x & 3u) != tag) v[k] = ld_pkt(src + k * 32 + lane);
            uint32_t bad = 0;
#pragma unroll
            for (int k = 0; k < 15; k++) bad |= v[k].x ^ tag;
            if (__all_sync(0xffffffffu, (bad & 3u) == 0)) break;
            POLL_GUARD(it);
        }
        float s0 = 0.f, s1 = 0.f, s2 = 0.f, s3 = 0.f;
#pragma unroll
        for (int k = 0; k < 15; k++) { s0 += __uint_as_float(v[k].x); s1 += __uint_as_float(v[k].y); s2 += __uint_as_float(v[k].z); s3 += __uint_as_float(v[k].w); }
        sts128(sb + SC_RED + ht * 16, __float_as_uint(s0), __float_as_uint(s1), __float_as_uint(s2), __float_as_uint(s3));
        bar_sync(10, 128);
        if (own) {
            const uint32_t ra = sb + SC_RED + (tok * 4 + ((c & 7) >> 1)) * 16 + ((c >> 3) * 2 + (c & 1)) * 4;
            const float y = rbf((__uint_as_float(lds32(ra)) + __uint_as_float(lds32(ra + 512))) + (__uint_as_float(lds32(ra + 1024)) + __uint_as_float(lds32(ra + 1536))));
            const float b = rbf(xv + rbf(y * rs));
            mbar_wait(bar_out + 8 * (row >> 8));
            const float a = bf_lo(lds16(sb + SC_OUT + (row >> 8) * OUT_STAGE + (c >> 3) * OUT_HALF + (c & 7) * 288 + (row & 7) * 32 + ((row >> 5) & 1) * 16
                                        + ((row >> 7) & 1) * 8 + ((row >> 3) & 1) * 4 + ((row >> 4) & 1) * 2));
            *(unsigned short*)(p.out + row * DM + 16 * slab + c) = (unsigned short)pack_bf16(gt * a + rbf(om * b), 0.f);
        }
    }
}

__device__ __forceinline__ void conv_main(const Params& p, uint32_t sb, int cb, int warp, uint32_t t0, float (&kv)[21]) {
    const int lane = threadIdx.x & 31;
    asm volatile("setmaxnreg.inc.sync.aligned.u32 168;");
    mbar_wait(sb + SB_PRE);
    if (warp >= 4) {
#pragma unroll 1
        for (int own = 0;; own = 1) {
            ktables(kv, sb + SC_KT + (warp - 4 + 4 * own) * KT_BYTES);
            if (own) break;
            bar_arrive(2 + warp, 64);
            mbar_wait(sb + SB_UT + 8);
            const uint32_t tag = lds32(sb + SC_TAG);
            const uint4* src = p.scr->kx + (4 * cb + warp - 4) * 128 + lane;
            while (clk() - t0 < KDELAY) __nanosleep(50);
            uint4 x[4];
            for (int it = 0;;) {
                x[0] = ld_pkt(src); x[1] = ld_pkt(src + 32); x[2] = ld_pkt(src + 64); x[3] = ld_pkt(src + 96);
                if (__all_sync(0xffffffffu, ((x[0].w ^ tag) | (x[1].w ^ tag) | (x[2].w ^ tag) | (x[3].w ^ tag)) == 0)) break;
                POLL_GUARD(it);
            }
#pragma unroll
            for (int i = 0; i < 3; i++) {
                kv[6 * i] = bf_lo(x[i].x); kv[6 * i + 1] = bf_hi(x[i].x); kv[6 * i + 2] = bf_lo(x[i].y); kv[6 * i + 3] = bf_hi(x[i].y);
                kv[6 * i + 4] = bf_lo(x[i].z); kv[6 * i + 5] = bf_hi(x[i].z);
            }
            kv[17] = bf_lo(x[3].x); kv[18] = bf_hi(x[3].x); kv[19] = bf_lo(x[3].y); kv[20] = bf_hi(x[3].y);
        }
    }
    ktable8(kv, sb + SC_KT + warp * KT_BYTES);
    conv_warp(sb, warp);
}

__device__ __forceinline__ void ffn_cta(const Params& p, const CUtensorMap* mR, const CUtensorMap* mG64, const CUtensorMap* mU64, const CUtensorMap* mG16,
                                        const CUtensorMap* mU16, const CUtensorMap* mWd, uint32_t sb, int f, int warp, uint32_t t0, const float (&kv)[21], int ci) {
    const int tid = threadIdx.x, lane = tid & 31, g = lane >> 2, t = lane & 3, mi = lane >> 3, r8 = lane & 7;
    const bool wide = f < 48;
    const int nunit = wide ? 10 : 8;
    const uint32_t bar_w = sb + SF_BAR, bar_d = bar_w + 72, bar_r = bar_w + 112, bar_sel = bar_w + 152, bar_free = bar_w + 160, bar_kg = bar_w + 184, bar_tk = bar_w + 192;
    uint32_t tag;
    uint4* const pdst = p.scr->part + (3 * warp * NFFN + f) * 32 + lane;
    auto clear_part = [&]() { st_pkt(pdst, 0, 0, 0, 0); st_pkt(pdst + NFFN * 32, 0, 0, 0, 0); st_pkt(pdst + 2 * NFFN * 32, 0, 0, 0, 0); };
    if (warp == 13) {
        if (lane == 0) {
#pragma unroll
            for (int i = 0; i < 14; i++) mbar_init(bar_w + 8 * i, 1);
            mbar_init(bar_sel, f >= 44 ? 5 : 4); mbar_init(bar_free, nunit); mbar_init(bar_free + 8, nunit); mbar_init(bar_free + 16, nunit); mbar_init(bar_kg, nunit); mbar_init(bar_tk, 1);
            mbar_fence_init();
        }
        __syncwarp();
        cluster_arrive_relaxed();
        cluster_wait();
        if (lane == 0) {
            spin_until(t0, FDELAY);
            prefetch_map(mG64); prefetch_map(mU64); prefetch_map(mG16); prefetch_map(mU16); prefetch_map(mWd);
            spin_until(t0, WDELAY);
#pragma unroll 1
            for (int n = 0; n < 9; n++) {
                if (n >= WWIN) { int it = 0; while (!mbar_test(bar_w + 8 * (n - WWIN)) && !mbar_test(bar_free)) { SPIN; POLL_GUARD(it); } }
                if (n == 4) mbar_wait(bar_kg);
                if (n == 8) mbar_wait(bar_sel);
                const uint32_t b = bar_w + 8 * n, d = sb + n * PIECE;
                mbar_expect(b, wide ? PIECE : 16384);
                tma2d(d, mG64, 64 * f, 64 * n, b); tma2d(d + 8192, mU64, 64 * f, 64 * n, b);
                if (wide) { tma2d(d + 16384, mG16, 3840 + 16 * f, 64 * n, b); tma2d(d + 18432, mU16, 3840 + 16 * f, 64 * n, b); }
            }
#pragma unroll 1
            for (int i = 0; i < nunit / 2; i++) {
                if (i < 2) { int it = 0; while (!mbar_test(bar_w + 8 * (9 + i - WWIN)) && !mbar_test(bar_free)) { SPIN; POLL_GUARD(it); } }
                else mbar_wait(bar_free + 8 * (i - 2));
                mbar_expect(bar_d + 8 * i, 18432);
                tma2d(i < 2 ? sb + SF_R + i * 18432 : sb + (i - 2) * PIECE, mWd, 0, 9 * (i < 4 ? 64 * f + 16 * i : 3840 + 16 * f), bar_d + 8 * i);
            }
        }
        return;
    }
    if (warp >= 10) {
        const int ng = f >= 44 ? 5 : 4, r0 = f >= 44 ? 1408 + 40 * (f - 44) : 32 * f;
        const int grp = warp == 12 ? 4 : warp < 12 ? warp - 10 : warp - 12;
        const uint32_t rows = grp < 4 ? sb + SF_R + grp * 9216 : sb + SF_R4;
        const int i = 32 * grp + lane;
        if (lane == 0) { mbar_init(bar_r + 8 * grp, 1); mbar_fence_init(); mbar_expect(bar_r + 8 * grp, 9216); }
        __syncwarp();
        cluster_arrive_relaxed();
        if (grp == 4) {
#pragma unroll 1
            for (int k = lane; k < 256; k += 32) sts128(sb + SF_LIST + k * 16, 0, 0, 0, 0);
        }
        uint4 w;
        spin_until(t0, RDELAY);
        if (lane == 0 && grp < ng) tma2d(rows, mR, 0, 9 * (r0 + 8 * grp), bar_r + 8 * grp);
        if (i < 144) w = ldg128((const uint4*)(i < 72 ? p.wr : p.gatew - DM) + i);
        if (i == 159) w.x = take_ticket(&p.scr->launch);
        if (grp < ng && t == 0) st_rlx32(&p.scr->rec[r0 + 8 * grp + g], 0);
        if (i < 144) sts128(sb + SF_WR + i * 16, w.x, w.y, w.z, w.w);
        if (i == 159) sts64(sb + SF_CNT, 0, tag_of(w.x));
        cluster_wait();
        bar_sync(10, 160);
        if (i == 159) mbar_arrive(bar_tk);
        if (grp < ng) {
            uint32_t wv[9][4];
            const uint32_t wa = sb + SF_WR + ((r8 >> 1) & 1) * 1152 + (2 * mi + (r8 & 1)) * 16;
#pragma unroll
            for (int k = 0; k < 9; k++) ldsm4(wv[k], wa + 128 * k);
            tag = lds32(sb + SF_TK);
            float c[3][4];
            mbar_wait(bar_r + 8 * grp);
#pragma unroll
            for (int k = 0; k < 18; k++) {
                const int line = 9 * r8 + (k >> 1);
                uint32_t a[4];
                ldsm4(a, rows + line * 128 + ((((4 * k + mi) ^ line) & 7) << 4));
                if (k < 3) mma_bf0(c[k], a[0], a[1], a[2], a[3], wv[k >> 1][2 * (k & 1)], wv[k >> 1][2 * (k & 1) + 1]);
                else mma_bf(c[k % 3], a[0], a[1], a[2], a[3], wv[k >> 1][2 * (k & 1)], wv[k >> 1][2 * (k & 1) + 1]);
            }
            const float s = (c[0][0] + c[0][3]) + (c[1][0] + c[1][3]) + (c[2][0] + c[2][3]);
            const uint32_t gg = __shfl_down_sync(0xffffffffu, pack_bf16(sigmoidf_(rbf(s)), 0.f), 1);
            uint32_t rb = pack_bf16(0.f, s);
            rb = (rb & 0x80000000u) ? ~rb : (rb | 0x80000000u);
            if (t == 0) st_rlx32(&p.scr->rec[r0 + 8 * grp + g], (rb & 0xffff0000u) | (tag << 14) | (gg & 0x3fffu));
            if (lane == 0) { sts32(sb + SF_CLK, clk()); mbar_arrive(bar_sel); }
        }
        if (warp >= 12) return;
        clear_part();
    } else {
        if (warp >= nunit) { cluster_arrive_relaxed(); cluster_wait(); }
        mbar_wait(bar_tk);
        tag = lds32(sb + SF_TK);
        if (warp < nunit) {
            uint4* const kdst = p.scr->kx + ci * 128 + lane;
            if (warp < nunit / 2) st_pkt(kdst + 96, pack_bf16(kv[17], kv[18]), pack_bf16(kv[19], kv[20]), 0, tag);
            else {
#pragma unroll
                for (int i = 0; i < 3; i++) st_pkt(kdst + 32 * i, pack_bf16(kv[6 * i], kv[6 * i + 1]), pack_bf16(kv[6 * i + 2], kv[6 * i + 3]), pack_bf16(kv[6 * i + 4], kv[6 * i + 5]), tag);
            }
            __syncwarp();
            if (lane == 0) mbar_arrive(bar_kg);
        }
        clear_part();
        if (warp < 8) {
            uint32_t k[8];
            const uint32_t tg = tag << 14;
            mbar_wait(bar_sel);
            spin_until(lds32(sb + SF_CLK), PDELAY);
            for (int it = 0;;) {
                const uint4 a = ld_rlx128(&p.scr->rec[4 * tid]), b = ld_rlx128(&p.scr->rec[1024 + 4 * tid]);
                k[0] = a.x; k[1] = a.y; k[2] = a.z; k[3] = a.w; k[4] = b.x; k[5] = b.y; k[6] = b.z; k[7] = b.w;
                if (__all_sync(0xffffffffu, (((a.x ^ tg) | (a.y ^ tg) | (a.z ^ tg) | (a.w ^ tg) | (b.x ^ tg) | (b.y ^ tg) | (b.z ^ tg) | (b.w ^ tg)) & 0xc000u) == 0)) break;
                POLL_GUARD(it);
            }
#pragma unroll
            for (int i = 0; i < 8; i++) k[i] = (k[i] & 0xffff0000u) | (uint32_t)(2047 - 1024 * (i >> 2) - (i & 3) - 4 * tid);
            const uint32_t m0 = __reduce_max_sync(0xffffffffu, max(max(k[0], k[1]), max(k[2], k[3]))), m1 = __reduce_max_sync(0xffffffffu, max(max(k[4], k[5]), max(k[6], k[7])));
            if (lane == 0) sts64(sb + SF_MAX + warp * 8, m0, m1);
            bar_sync(7, 256);
            uint32_t thr;
            {
                const uint32_t m = lds32(sb + SF_MAX + (lane & 15) * 4);
                int rk = 0;
#pragma unroll
                for (int i = 0; i < 4; i++) { const uint4 x = lds128(sb + SF_MAX + 16 * i); rk += (x.x > m) + (x.y > m) + (x.z > m) + (x.w > m); }
                thr = __reduce_max_sync(0xffffffffu, rk == 7 ? m : 0u);
            }
#pragma unroll
            for (int i = 0; i < 8; i++)
                if (k[i] >= thr) { uint32_t s; asm volatile("atom.shared.add.u32 %0, [%1], 1;" : "=r"(s) : "r"(sb + SF_CNT) : "memory"); sts32(sb + SF_LIST + 4 * s, k[i]); }
            bar_sync(7, 256);
            const int n = lds32(sb + SF_CNT);
            uint32_t key = 0;
#pragma unroll 1
            for (int base = 0; base < n; base += 32) {
                const uint32_t m = lds32(sb + SF_LIST + (base + lane) * 4);
                int rk = 0;
#pragma unroll 1
                for (int i = 0; i < n; i += 8) {
                    const uint4 x = lds128(sb + SF_LIST + 4 * i), y = lds128(sb + SF_LIST + 4 * i + 16);
                    rk += (x.x > m) + (x.y > m) + (x.z > m) + (x.w > m) + (y.x > m) + (y.y > m) + (y.z > m) + (y.w > m);
                }
                if (rk == warp && base + lane < n) key = m;
            }
            key = __reduce_max_sync(0xffffffffu, key);
            const uint4* xr = (const uint4*)(p.u + key_row(key) * DM);
            const uint4 x0 = ldg128(xr + lane), x1 = ldg128(xr + 32 + lane), x2 = ldg128(xr + 64 + r8);
            if (lane == 0) sts32(sb + SF_SEL + warp * 4, key | (tag << 11));
            bar_sync(7, 256);
            if (f == 0 && tid < 8) st_rlx32(&p.scr->sel[tid], lds32(sb + SF_SEL + tid * 4));
            const uint32_t xd = sb + SF_XS + warp * 1168 + lane * 16;
            sts128(xd, x0.x, x0.y, x0.z, x0.w); sts128(xd + 512, x1.x, x1.y, x1.z, x1.w);
            if (lane < 8) sts128(xd + 1024, x2.x, x2.y, x2.z, x2.w);
        }
        if (warp < nunit) {
            bar_sync(8, 32 * nunit);
            const int kr = 8 * (mi >> 1) + r8;
            uint32_t wa = warp < 8 ? sb + (mi & 1) * 8192 + kr * 128 + ((warp ^ r8) << 4) : sb + 16384 + (mi & 1) * 2048 + kr * 32 + (((warp ^ (r8 >> 2)) & 1) << 4);
            const uint32_t ws = warp < 8 ? 2048 : 512;
            uint32_t xa = sb + SF_XS + r8 * 1168 + mi * 16;
            float c0[4] = {0.f, 0.f, 0.f, 0.f}, c1[4] = {0.f, 0.f, 0.f, 0.f};
#pragma unroll 1
            for (int n = 0; n < 9; n++) {
                uint32_t x[2][4], a[4][4];
                ldsm4(x[0], xa); ldsm4(x[1], xa + 64);
                mbar_wait(bar_w + 8 * n);
#pragma unroll
                for (int s = 0; s < 4; s++) ldsm4t(a[s], wa + s * ws);
                mma_bf(c0, a[0][0], a[0][1], a[0][2], a[0][3], x[0][0], x[0][1]);
                mma_bf(c1, a[1][0], a[1][1], a[1][2], a[1][3], x[0][2], x[0][3]);
                mma_bf(c0, a[2][0], a[2][1], a[2][2], a[2][3], x[1][0], x[1][1]);
                mma_bf(c1, a[3][0], a[3][1], a[3][2], a[3][3], x[1][2], x[1][3]);
                if (n < 3) {
                    asm volatile("" :: "r"(a[0][0]), "r"(a[1][0]), "r"(a[2][0]), "r"(a[3][0]) : "memory");
                    __syncwarp();
                    if (lane == 0) mbar_arrive(bar_free + 8 * n);
                }
                wa += PIECE; xa += 128;
            }
            float h[2];
#pragma unroll
            for (int e = 0; e < 2; e++) {
                const float gv = rbf(c0[e] + c1[e]), uv = rbf(c0[2 + e] + c1[2 + e]);
                h[e] = rbf(gv * sigmoidf_(gv)) * uv;
            }
            uint32_t hp = pack_bf16(h[0], h[1]);
            asm volatile("movmatrix.sync.aligned.m8n8.trans.b16 %0, %0;" : "+r"(hp));
            sts32(sb + SF_H + (warp >> 1) * 256 + lane * 8 + (warp & 1) * 4, hp);
        }
    }
    bar_sync(9, 384);
    tag = lds32(sb + SF_TK);
    float d[6][4];
    uint32_t off[3];
#pragma unroll
    for (int j = 0; j < 3; j++) {
        const int tile = 3 * warp + j, line = 9 * (8 * (mi & 1) + r8) + (tile >> 2);
        off[j] = line * 128 + ((((2 * tile + (mi >> 1)) ^ line) & 7) << 4);
    }
#pragma unroll
    for (int j = 0; j < 6; j++) d[j][0] = d[j][1] = d[j][2] = d[j][3] = 0.f;
#pragma unroll 1
    for (int i = 0; i < nunit / 2; i++) {
        const uint2 hv = lds64(sb + SF_H + i * 256 + lane * 8);
        const uint32_t base = i < 2 ? sb + SF_R + i * 18432 : sb + (i - 2) * PIECE;
        mbar_wait(bar_d + 8 * i);
        uint32_t a[3][4];
#pragma unroll
        for (int j = 0; j < 3; j++) ldsm4t(a[j], base + off[j]);
#pragma unroll
        for (int j = 0; j < 3; j++) { mma_bf(d[2 * j], hv.x, 0u, hv.y, 0u, a[j][0], a[j][1]); mma_bf(d[2 * j + 1], hv.x, 0u, hv.y, 0u, a[j][2], a[j][3]); }
    }
#pragma unroll
    for (int j = 0; j < 3; j++) {
        st_pkt(pdst + j * NFFN * 32, (__float_as_uint(d[2 * j][0]) & ~3u) | tag, __float_as_uint(d[2 * j][1]), __float_as_uint(d[2 * j + 1][0]), __float_as_uint(d[2 * j + 1][1]));
    }
}

__global__ void __cluster_dims__(2, 1, 1) __launch_bounds__(NTHR, 1)
fused_kernel(const Params p, const __grid_constant__ CUtensorMap mU, const __grid_constant__ CUtensorMap mR, const __grid_constant__ CUtensorMap mG64,
             const __grid_constant__ CUtensorMap mU64, const __grid_constant__ CUtensorMap mG16, const __grid_constant__ CUtensorMap mU16,
             const __grid_constant__ CUtensorMap mWd) {
    extern __shared__ __align__(1024) uint8_t smem_raw[];
    const uint32_t sb = smem_u32(smem_raw);
    const uint32_t t0 = clk();
    const int bx = blockIdx.x;
    const int lane = threadIdx.x & 31, f = bx - FFN0, cb = bx < FFN0 ? bx : bx - NFFN;
    const bool ffn = (unsigned)f < NFFN;
    const int nch = (unsigned)f < 48 ? 5 : 4, c0 = ffn ? (nch == 5 ? 5 * f : 4 * f + 48) : 4 * cb;
    const int warp = warp_id();
    KParams kp;
    {
        const int w = threadIdx.x >> 5, h = w >= nch, c = c0 + w - nch * h;
        if (w < 2 * nch) kp = kload(p, 2 * (c & ~3) + (ffn ? 4 : 0) + (c & 3), h);
    }
    const int half = warp >= nch, j = warp - nch * half, ci = c0 + j;
    float kv[21];
    if (warp < 2 * nch) {
        const uint32_t stage = sb + (ffn ? SF_STG : SC_STG);
        cluster_arrive_relaxed();
        if (f == 0 && threadIdx.x < 8) st_rlx32(&p.scr->sel[lane], 0);
        float fin;
        kgen(kp, stage + warp * KG_STAGE, kv, fin, sb);
        cluster_wait();
        kswap(kv, fin, stage + warp * KG_STAGE, stage + (half ? j : warp + nch) * KG_STAGE, half, 2 + j, kp.dskip);
    }
    if (ffn) ffn_cta(p, &mR, &mG64, &mU64, &mG16, &mU16, &mWd, sb, f, warp, t0, kv, ci);
    else if (warp < 8) conv_main(p, sb, cb, warp, t0, kv);
    else conv_helper(p, &mU, sb, cb, warp - 8, t0);
}

typedef CUresult (*EncodeFn)(CUtensorMap*, CUtensorMapDataType, cuuint32_t, void*, const cuuint64_t*, const cuuint64_t*, const cuuint32_t*, const cuuint32_t*,
                             CUtensorMapInterleave, CUtensorMapSwizzle, CUtensorMapL2promotion, CUtensorMapFloatOOBfill);

CUtensorMap make_map(EncodeFn fn, const void* base, uint64_t inner, uint64_t outer, uint32_t bi, uint32_t bo, CUtensorMapSwizzle sw,
                     CUtensorMapL2promotion pr = CU_TENSOR_MAP_L2_PROMOTION_NONE) {
    CUtensorMap m;
    cuuint64_t dims[2] = {inner, outer};
    cuuint64_t strides[1] = {inner * 2};
    cuuint32_t box[2] = {bi, bo};
    cuuint32_t es[2] = {1, 1};
    fn(&m, CU_TENSOR_MAP_DATA_TYPE_BFLOAT16, 2, (void*)base, dims, strides, box, es, CU_TENSOR_MAP_INTERLEAVE_NONE, sw, pr, CU_TENSOR_MAP_FLOAT_OOB_FILL_NONE);
    return m;
}

}

extern "C" void kernel_launch(void* const* d_in, const int* in_sizes, int n_in, void* d_out, int out_size) {
    (void)in_sizes; (void)n_in; (void)out_size;
    static EncodeFn fn = nullptr;
    static Scratch* scr = nullptr;
    if (!fn) {
        void* ptr = nullptr; cudaDriverEntryPointQueryResult qr;
        cudaGetDriverEntryPoint("cuTensorMapEncodeTiled", &ptr, cudaEnableDefault, &qr);
        fn = (EncodeFn)ptr;
        cudaGetSymbolAddress((void**)&scr, g_scr);
        cudaFuncSetAttribute(fused_kernel, cudaFuncAttributeMaxDynamicSharedMemorySize, SMEM_BYTES);
    }
    typedef const __nv_bfloat16* bp;
    Params p;
    p.u = (bp)d_in[0]; p.Are = (bp)d_in[1]; p.Aim = (bp)d_in[2]; p.Bre = (bp)d_in[3]; p.Bim = (bp)d_in[4]; p.Cre = (bp)d_in[5]; p.Cim = (bp)d_in[6];
    p.logdt = (bp)d_in[7]; p.Dskip = (bp)d_in[8]; p.wr = (bp)d_in[10]; p.gatew = (bp)d_in[14];
    p.out = (__nv_bfloat16*)d_out; p.scr = scr;
    CUtensorMap mU;
    {
        cuuint64_t dims[5] = {DM, 8, 2, L_SEQ / 128, 8};
        cuuint64_t strides[4] = {16 * DM * 2, DM * 2, 128 * DM * 2, 2 * DM * 2};
        cuuint32_t box[5] = {16, 4, 2, 4, 8};
        cuuint32_t es[5] = {1, 1, 1, 1, 1};
        fn(&mU, CU_TENSOR_MAP_DATA_TYPE_BFLOAT16, 5, d_in[0], dims, strides, box, es, CU_TENSOR_MAP_INTERLEAVE_NONE, CU_TENSOR_MAP_SWIZZLE_32B,
           CU_TENSOR_MAP_L2_PROMOTION_NONE, CU_TENSOR_MAP_FLOAT_OOB_FILL_NONE);
    }
    const CUtensorMap mR = make_map(fn, d_in[0], 64, L_SEQ * 9, 64, 72, CU_TENSOR_MAP_SWIZZLE_128B);
    const CUtensorMap mG64 = make_map(fn, d_in[11], FF, DM, 64, 64, CU_TENSOR_MAP_SWIZZLE_128B);
    const CUtensorMap mU64 = make_map(fn, d_in[12], FF, DM, 64, 64, CU_TENSOR_MAP_SWIZZLE_128B);
    const CUtensorMap mG16 = make_map(fn, d_in[11], FF, DM, 16, 64, CU_TENSOR_MAP_SWIZZLE_32B, CU_TENSOR_MAP_L2_PROMOTION_L2_128B);
    const CUtensorMap mU16 = make_map(fn, d_in[12], FF, DM, 16, 64, CU_TENSOR_MAP_SWIZZLE_32B, CU_TENSOR_MAP_L2_PROMOTION_L2_128B);
    const CUtensorMap mWd = make_map(fn, d_in[13], 64, FF * 9, 64, 144, CU_TENSOR_MAP_SWIZZLE_128B);
    fused_kernel<<<NCTA, NTHR, SMEM_BYTES>>>(p, mU, mR, mG64, mU64, mG16, mU16, mWd);
}
```

```cpp
#include <cuda_runtime.h>
#include <cuda_bf16.h>
#include <cuda_fp16.h>
#include <cuda.h>
#include <stdint.h>

#define RDELAY 1000
#define UDELAY 500
#define WDELAY 1800
#define PDELAY 900
#define KDELAY 7200
#define SPIN
#define FDELAY 600
#define DUPA lds32v(k1 + 512 * j1)
#define PACE 20
#define VDELAY 1000
#define PFP 600
#define PFN 4
#define GDELAY 0
#define TDELAY 0
#define TSTEP 0
#define KSLEEP 50
#define CLR 1
#define STN 2
#define WWIN 4

namespace {

#define JBAR 0
#define UNR 8
constexpr int DUNR = UNR;
constexpr int L_SEQ = 2048, DM = 576, NST = 128, FF = 4608;
constexpr int NCTA = 132, NFFN = 60, FFN0 = 8, NTHR = 512;

struct Scratch {
    unsigned launch; unsigned pad0[31];
    uint32_t sel[32];
    uint32_t zero[72 * 8];
    uint32_t rec[L_SEQ];
    uint4 kx[288 * 6 * 32];
    uint2 part[36 * NFFN * 32];
};
__device__ Scratch g_scr;

struct Params {
    const __nv_bfloat16 *Are, *Aim, *Bre, *Bim, *Cre, *Cim, *logdt, *Dskip, *u, *wr, *gatew;
    __nv_bfloat16* out;
    Scratch* scr;
};

__device__ __forceinline__ uint32_t smem_u32(const void* p) { return (uint32_t)__cvta_generic_to_shared(p); }
__device__ __forceinline__ uint32_t pack_bf16(float lo, float hi) { uint32_t r; asm("cvt.rn.bf16x2.f32 %0, %1, %2;" : "=r"(r) : "f"(hi), "f"(lo)); return r; }
__device__ __forceinline__ uint32_t pack_f16(float lo, float hi) { uint32_t r; asm("cvt.rn.f16x2.f32 %0, %1, %2;" : "=r"(r) : "f"(hi), "f"(lo)); return r; }
__device__ __forceinline__ float bf_lo(uint32_t w) { return __uint_as_float(w << 16); }
__device__ __forceinline__ float bf_hi(uint32_t w) { return __uint_as_float(w & 0xffff0000u); }
__device__ __forceinline__ uint32_t cvt_bf16(float x) { uint32_t r; asm volatile("cvt.rn.bf16x2.f32 %0, %1, %1;" : "=r"(r) : "f"(x)); return r; }
__device__ __forceinline__ float rbf(float x) { return bf_lo(pack_bf16(x, 0.f)); }
__device__ __forceinline__ uint32_t hmul2(uint32_t a, uint32_t b) { __nv_bfloat162 r = __hmul2_rn(*(__nv_bfloat162*)&a, *(__nv_bfloat162*)&b); return *(uint32_t*)&r; }
__device__ __forceinline__ uint32_t hadd2(uint32_t a, uint32_t b) { __nv_bfloat162 r = __hadd2_rn(*(__nv_bfloat162*)&a, *(__nv_bfloat162*)&b); return *(uint32_t*)&r; }
__device__ __forceinline__ uint32_t hfma2(uint32_t a, uint32_t b, uint32_t c) { uint32_t r; asm("fma.rn.bf16x2 %0, %1, %2, %3;" : "=r"(r) : "r"(a), "r"(b), "r"(c)); return r; }
__device__ __forceinline__ uint32_t hsub2(uint32_t a, uint32_t b) { __nv_bfloat162 r = __hsub2_rn(*(__nv_bfloat162*)&a, *(__nv_bfloat162*)&b); return *(uint32_t*)&r; }
__device__ __forceinline__ void mma_bf(float (&c)[4], uint32_t a0, uint32_t a1, uint32_t a2, uint32_t a3, uint32_t b0, uint32_t b1) {
    asm("mma.sync.aligned.m16n8k16.row.col.f32.bf16.bf16.f32 {%0,%1,%2,%3}, {%4,%5,%6,%7}, {%8,%9}, {%0,%1,%2,%3};"
        : "+f"(c[0]), "+f"(c[1]), "+f"(c[2]), "+f"(c[3]) : "r"(a0), "r"(a1), "r"(a2), "r"(a3), "r"(b0), "r"(b1));
}
__device__ __forceinline__ void mma_bf0(float (&c)[4], uint32_t a0, uint32_t a1, uint32_t a2, uint32_t a3, uint32_t b0, uint32_t b1) {
    asm("mma.sync.aligned.m16n8k16.row.col.f32.bf16.bf16.f32 {%0,%1,%2,%3}, {%4,%5,%6,%7}, {%8,%9}, {%10,%10,%10,%10};"
        : "=f"(c[0]), "=f"(c[1]), "=f"(c[2]), "=f"(c[3]) : "r"(a0), "r"(a1), "r"(a2), "r"(a3), "r"(b0), "r"(b1), "f"(0.f));
}
__device__ __forceinline__ void mma_bf8(float (&c)[4], uint32_t a0, uint32_t a1, uint32_t b0) {
    asm("mma.sync.aligned.m16n8k8.row.col.f32.bf16.bf16.f32 {%0,%1,%2,%3}, {%4,%5}, {%6}, {%0,%1,%2,%3};"
        : "+f"(c[0]), "+f"(c[1]), "+f"(c[2]), "+f"(c[3]) : "r"(a0), "r"(a1), "r"(b0));
}
__device__ __forceinline__ void mma_f16(float (&c)[4], uint32_t a0, uint32_t a1, uint32_t a2, uint32_t a3, uint32_t b0, uint32_t b1) {
    asm("mma.sync.aligned.m16n8k16.row.col.f32.f16.f16.f32 {%0,%1,%2,%3}, {%4,%5,%6,%7}, {%8,%9}, {%0,%1,%2,%3};"
        : "+f"(c[0]), "+f"(c[1]), "+f"(c[2]), "+f"(c[3]) : "r"(a0), "r"(a1), "r"(a2), "r"(a3), "r"(b0), "r"(b1));
}
__device__ __forceinline__ uint32_t lds16(uint32_t a) { uint32_t v; asm volatile("ld.shared.u16 %0, [%1];" : "=r"(v) : "r"(a)); return v; }
__device__ __forceinline__ uint32_t lds8(uint32_t a) { uint32_t v; asm volatile("ld.shared.u8 %0, [%1];" : "=r"(v) : "r"(a)); return v; }
__device__ __forceinline__ uint32_t lds32(uint32_t a) { uint32_t v; asm volatile("ld.shared.u32 %0, [%1];" : "=r"(v) : "r"(a)); return v; }
__device__ __forceinline__ uint32_t lds32v(uint32_t a) { uint32_t v; asm volatile("ld.volatile.shared.u32 %0, [%1];" : "=r"(v) : "r"(a)); return v; }
__device__ __forceinline__ uint2 lds64(uint32_t a) { uint2 v; asm volatile("ld.shared.v2.u32 {%0,%1}, [%2];" : "=r"(v.x), "=r"(v.y) : "r"(a)); return v; }
__device__ __forceinline__ uint4 lds128(uint32_t a) { uint4 v; asm volatile("ld.shared.v4.u32 {%0,%1,%2,%3}, [%4];" : "=r"(v.x), "=r"(v.y), "=r"(v.z), "=r"(v.w) : "r"(a)); return v; }
__device__ __forceinline__ void ldsm4(uint32_t (&r)[4], uint32_t a) {
    asm volatile("ldmatrix.sync.aligned.m8n8.x4.shared.b16 {%0,%1,%2,%3}, [%4];" : "=r"(r[0]), "=r"(r[1]), "=r"(r[2]), "=r"(r[3]) : "r"(a));
}
__device__ __forceinline__ void ldsm4t(uint32_t (&r)[4], uint32_t a) {
    asm volatile("ldmatrix.sync.aligned.m8n8.x4.trans.shared.b16 {%0,%1,%2,%3}, [%4];" : "=r"(r[0]), "=r"(r[1]), "=r"(r[2]), "=r"(r[3]) : "r"(a));
}
__device__ __forceinline__ void sts16(uint32_t a, uint32_t v) { asm volatile("st.shared.u16 [%0], %1;" :: "r"(a), "r"(v) : "memory"); }
__device__ __forceinline__ void sts32(uint32_t a, uint32_t v) { asm volatile("st.shared.u32 [%0], %1;" :: "r"(a), "r"(v) : "memory"); }
__device__ __forceinline__ void sts64(uint32_t a, uint32_t x, uint32_t y) { asm volatile("st.shared.v2.u32 [%0], {%1,%2};" :: "r"(a), "r"(x), "r"(y) : "memory"); }
__device__ __forceinline__ void sts128(uint32_t a, uint32_t x, uint32_t y, uint32_t z, uint32_t w) {
    asm volatile("st.shared.v4.u32 [%0], {%1,%2,%3,%4};" :: "r"(a), "r"(x), "r"(y), "r"(z), "r"(w) : "memory");
}
__device__ __forceinline__ void stsm2(uint32_t a, uint32_t x, uint32_t y) {
    asm volatile("stmatrix.sync.aligned.m8n8.x2.shared.b16 [%0], {%1,%2};" :: "r"(a), "r"(x), "r"(y) : "memory");
}
__device__ __forceinline__ void stsm4t(uint32_t a, uint32_t r0, uint32_t r1, uint32_t r2, uint32_t r3) {
    asm volatile("stmatrix.sync.aligned.m8n8.x4.trans.shared.b16 [%0], {%1,%2,%3,%4};" :: "r"(a), "r"(r0), "r"(r1), "r"(r2), "r"(r3) : "memory");
}
__device__ __forceinline__ void st_async64(uint32_t a, uint32_t x, uint32_t y, uint32_t bar) {
    asm volatile("st.async.weak.shared::cluster.mbarrier::complete_tx::bytes.v2.b32 [%0], {%1,%2}, [%3];" :: "r"(a), "r"(x), "r"(y), "r"(bar) : "memory");
}
__device__ __forceinline__ void st_async128(uint32_t a, uint32_t x, uint32_t y, uint32_t z, uint32_t w, uint32_t bar) {
    asm volatile("st.async.weak.shared::cluster.mbarrier::complete_tx::bytes.v4.b32 [%0], {%1,%2,%3,%4}, [%5];" :: "r"(a), "r"(x), "r"(y), "r"(z), "r"(w), "r"(bar) : "memory");
}
__device__ __forceinline__ void mbar_init(uint32_t b, uint32_t cnt) { asm volatile("mbarrier.init.shared::cta.b64 [%0], %1;" :: "r"(b), "r"(cnt) : "memory"); }
__device__ __forceinline__ void mbar_fence_init() { asm volatile("fence.mbarrier_init.release.cluster;" ::: "memory"); }
__device__ __forceinline__ void mbar_expect(uint32_t b, uint32_t bytes) { asm volatile("mbarrier.arrive.expect_tx.shared::cta.b64 _, [%0], %1;" :: "r"(b), "r"(bytes) : "memory"); }
__device__ __forceinline__ void mbar_arrive(uint32_t b) { asm volatile("mbarrier.arrive.shared::cta.b64 _, [%0];" :: "r"(b) : "memory"); }
__device__ __forceinline__ void mbar_wait(uint32_t b) {
    asm volatile("{ .reg .pred p; .reg .u32 n; mov.u32 n, 0;\n"
                 "W: mbarrier.try_wait.parity.shared::cta.b64 p, [%0], 0; @p bra D; add.u32 n, n, 1; setp.lt.u32 p, n, 4000000; @p bra W; trap;\n"
                 "D: }" :: "r"(b) : "memory");
}
__device__ __forceinline__ bool mbar_test(uint32_t b) {
    uint32_t d; asm volatile("{ .reg .pred p; mbarrier.test_wait.parity.shared::cta.b64 p, [%1], 0; selp.u32 %0, 1, 0, p; }" : "=r"(d) : "r"(b) : "memory"); return d;
}
__device__ __forceinline__ void tma2d(uint32_t dst, const CUtensorMap* m, int c0, int c1, uint32_t bar) {
    asm volatile("cp.async.bulk.tensor.2d.shared::cluster.global.mbarrier::complete_tx::bytes [%0], [%1, {%3, %4}], [%2];"
                 :: "r"(dst), "l"(m), "r"(bar), "r"(c0), "r"(c1) : "memory");
}
__device__ __forceinline__ void tma5d(uint32_t dst, const CUtensorMap* m, int c0, int c1, int c2, int c3, int c4, uint32_t bar) {
    asm volatile("cp.async.bulk.tensor.5d.shared::cluster.global.mbarrier::complete_tx::bytes [%0], [%1, {%3, %4, %5, %6, %7}], [%2];"
                 :: "r"(dst), "l"(m), "r"(bar), "r"(c0), "r"(c1), "r"(c2), "r"(c3), "r"(c4) : "memory");
}
__device__ __forceinline__ void pf2d(const CUtensorMap* m, int c0, int c1) {
    asm volatile("cp.async.bulk.prefetch.tensor.2d.L2.global [%0, {%1, %2}];" :: "l"(m), "r"(c0), "r"(c1) : "memory");
}
__device__ __forceinline__ uint32_t mapa(uint32_t a, uint32_t rank) { uint32_t r; asm("mapa.shared::cluster.u32 %0, %1, %2;" : "=r"(r) : "r"(a), "r"(rank)); return r; }
__device__ __forceinline__ void prefetch_map(const CUtensorMap* m) { asm volatile("prefetch.tensormap [%0];" :: "l"(m) : "memory"); }
__device__ __forceinline__ void bar_sync(int id, int n) { asm volatile("bar.sync %0, %1;" :: "r"(id), "r"(n) : "memory"); }
__device__ __forceinline__ void bar_arrive(int id, int n) { asm volatile("bar.arrive %0, %1;" :: "r"(id), "r"(n) : "memory"); }
__device__ __forceinline__ void cluster_arrive_relaxed() { asm volatile("barrier.cluster.arrive.relaxed.aligned;" ::: "memory"); }
__device__ __forceinline__ void cluster_wait() { asm volatile("barrier.cluster.wait.aligned;" ::: "memory"); }
__device__ __forceinline__ uint32_t ld_rlx32(const void* p) { uint32_t v; asm volatile("ld.relaxed.gpu.global.u32 %0, [%1];" : "=r"(v) : "l"(p) : "memory"); return v; }
__device__ __forceinline__ uint4 ld_rlx128(const void* p) {
    uint4 v; asm volatile("ld.relaxed.gpu.global.v4.u32 {%0,%1,%2,%3}, [%4];" : "=r"(v.x), "=r"(v.y), "=r"(v.z), "=r"(v.w) : "l"(p) : "memory"); return v;
}
__device__ __forceinline__ uint32_t ld_acq32(const void* p) { uint32_t v; asm volatile("ld.acquire.gpu.global.u32 %0, [%1];" : "=r"(v) : "l"(p) : "memory"); return v; }
__device__ __forceinline__ void red_bf2(void* p, uint32_t v) { asm volatile("red.relaxed.gpu.global.add.noftz.bf16x2 [%0], %1;" :: "l"(p), "r"(v) : "memory"); }
__device__ __forceinline__ uint32_t take_ticket(unsigned* p) { uint32_t v; asm volatile("atom.relaxed.gpu.global.add.u32 %0, [%1], 1;" : "=r"(v) : "l"(p) : "memory"); return v; }
__device__ __forceinline__ void st_rlx32(void* p, uint32_t v) { asm volatile("st.relaxed.gpu.global.u32 [%0], %1;" :: "l"(p), "r"(v) : "memory"); }
__device__ __forceinline__ void st_pkt(void* p, uint32_t x, uint32_t y, uint32_t z, uint32_t w) {
    asm volatile("{ .reg .b64 lo, hi; .reg .b128 v; mov.b64 lo, {%1, %2}; mov.b64 hi, {%3, %4}; mov.b128 v, {lo, hi}; st.relaxed.gpu.global.b128 [%0], v; }"
                 :: "l"(p), "r"(x), "r"(y), "r"(z), "r"(w) : "memory");
}
__device__ __forceinline__ uint4 ld_pkt(const void* p) {
    uint4 r;
    asm volatile("{ .reg .b64 lo, hi; .reg .b128 v; ld.relaxed.gpu.global.b128 v, [%4]; mov.b128 {lo, hi}, v; mov.b64 {%0, %1}, lo; mov.b64 {%2, %3}, hi; }"
                 : "=r"(r.x), "=r"(r.y), "=r"(r.z), "=r"(r.w) : "l"(p) : "memory");
    return r;
}
__device__ __forceinline__ void st_pkt8(void* p, uint32_t x, uint32_t y) {
    asm volatile("{ .reg .b64 v; mov.b64 v, {%1, %2}; st.relaxed.gpu.global.b64 [%0], v; }" :: "l"(p), "r"(x), "r"(y) : "memory");
}
__device__ __forceinline__ uint2 ld_pkt8(const void* p) {
    uint2 r; asm volatile("{ .reg .b64 v; ld.relaxed.gpu.global.b64 v, [%2]; mov.b64 {%0, %1}, v; }" : "=r"(r.x), "=r"(r.y) : "l"(p) : "memory"); return r;
}
__device__ __forceinline__ uint32_t tag_of(uint32_t ticket) { return ticket / NCTA % 3u + 1u; }
__device__ __forceinline__ uint2 ldg64(const void* p) { uint2 v; asm volatile("ld.global.nc.v2.u32 {%0,%1}, [%2];" : "=r"(v.x), "=r"(v.y) : "l"(p)); return v; }
__device__ __forceinline__ uint4 ldg128(const void* p) { uint4 v; asm volatile("ld.global.nc.v4.u32 {%0,%1,%2,%3}, [%4];" : "=r"(v.x), "=r"(v.y), "=r"(v.z), "=r"(v.w) : "l"(p)); return v; }
__device__ __forceinline__ uint32_t ldg32(const void* p) { uint32_t v; asm volatile("ld.global.nc.u32 %0, [%1];" : "=r"(v) : "l"(p)); return v; }
__device__ __forceinline__ uint32_t ldg16(const void* p) { uint32_t v; asm volatile("ld.global.nc.u16 %0, [%1];" : "=r"(v) : "l"(p)); return v; }
__device__ __forceinline__ int warp_id() { return __shfl_sync(0xffffffffu, threadIdx.x >> 5, 0); }
__device__ __forceinline__ uint32_t clk() { uint32_t t; asm volatile("mov.u32 %0, %clock;" : "=r"(t) :: "memory"); return t; }
__device__ __forceinline__ void spin_until(uint32_t t0, uint32_t d) { while (clk() - t0 < d) { SPIN; } }
__device__ __forceinline__ float sigmoidf_(float x) { return __fdividef(1.0f, 1.0f + __expf(-x)); }
__device__ __forceinline__ int key_row(uint32_t key) { return 2047 - (int)(key & 2047u); }
__device__ __forceinline__ float key_val(uint32_t key) {
    const uint32_t o = key & 0xffff0000u; return __uint_as_float((o & 0x80000000u) ? (o & 0x7fffffffu) : (~o & 0xffff0000u));
}
#define RARE(x) __builtin_expect(!!(x), 0)
#define POLL_GUARD(it) if (++(it) > (1 << 20)) __trap()

constexpr int UT_PL = 2240, UT_STRIDE = 4544;
constexpr int KT_P = 0, KT_P4 = 544 * 4, KT_P8 = KT_P4 + 172 * 4, KT_BYTES = KT_P8 + 140 * 4;
constexpr int KG_ROW = 272, KG_STAGE = 33 * KG_ROW;
constexpr int OUT_HALF = 2368, OUT_STAGE = 2 * OUT_HALF;
constexpr int SC_UTILE = 0;
constexpr int SC_UT = 32768;
constexpr int SC_STG = SC_UT + 8 * UT_STRIDE;
constexpr int SC_KT = SC_STG + 8 * KG_STAGE;
constexpr int SC_OUT = SC_KT + 8 * KT_BYTES;
constexpr int SC_RED = SC_OUT + 8 * OUT_STAGE;
constexpr int SC_CT = SC_RED + 2048;
constexpr int SC_BAR = SC_CT + 2560;
constexpr int SB_UT = SC_BAR + 32, SB_PRE = SC_BAR + 48, SB_OUT = SC_BAR + 64, SC_KEY = SC_BAR + 128, SC_TAG = SC_BAR + 160;
constexpr int SC_END = SC_BAR + 256;
static_assert(SC_STG % 128 == 0 && SC_OUT % 128 == 0 && SC_KT % 16 == 0, "align");
constexpr int PIECE = 20480;
constexpr int SF_R = 9 * PIECE;
constexpr int SF_XS = SF_R + 36864;
constexpr int SF_STG = 4 * PIECE, SF_R4 = 8 * PIECE + 8192;
constexpr int SF_RED = 4 * PIECE, SF_LIST = SF_XS, SF_WR = SF_XS + 4096;
constexpr int SF_H = SF_XS + 9344;
constexpr int SF_BAR = SF_H + 1280;
constexpr int SF_MAX = SF_BAR + 208, SF_CNT = SF_MAX + 64, SF_TK = SF_CNT + 4, SF_CLK = SF_CNT + 8, SF_SEL = SF_CNT + 16;
constexpr int SF_END = SF_SEL + 32;
constexpr int SM_TIM = SF_END;
constexpr int SMEM_BYTES = SF_END + 256;
static_assert(SF_STG + 10 * KG_STAGE <= SF_R4 && SMEM_BYTES <= 232448 && SC_END <= SF_END, "smem");

struct cplx { float re, im; };
struct h2c { uint32_t re, im; };
__device__ __forceinline__ cplx csq(cplx a) {
    cplx r; r.re = a.re * a.re - a.im * a.im;
    asm("{ .reg .f32 t; mul.f32 t, %1, %2; mul.f32 %0, t, 0f40000000; }" : "=f"(r.im) : "f"(a.re), "f"(a.im));
    return r;
}
__device__ __forceinline__ float ex2(float x) { float m; asm("ex2.approx.ftz.f32 %0, %1;" : "=f"(m) : "f"(x)); return m; }
__device__ __forceinline__ cplx cexp2(float x, float y) {
    const float m = ex2(x);
    cplx o; o.re = m * __cosf(y); o.im = m * __sinf(y); return o;
}
__device__ __forceinline__ h2c hpack(cplx a, cplx b) { h2c r; r.re = pack_f16(a.re, b.re); r.im = pack_f16(a.im, b.im); return r; }
__device__ __forceinline__ h2c hmulc(h2c a, h2c m) {
    h2c r;
    asm("{ .reg .b32 s, t; mul.f16x2 s, %3, %5; mul.f16x2 t, %3, %4; neg.f16x2 s, s; fma.rn.f16x2 %0, %2, %4, s; fma.rn.f16x2 %1, %2, %5, t; }"
        : "=&r"(r.re), "=r"(r.im) : "r"(a.re), "r"(a.im), "r"(m.re), "r"(m.im));
    return r;
}
__device__ __forceinline__ h2c hmulj(h2c a, h2c m) {
    h2c r;
    asm("{ .reg .b32 s, t; mul.f16x2 s, %3, %5; mul.f16x2 t, %2, %5; neg.f16x2 t, t; fma.rn.f16x2 %0, %2, %4, s; fma.rn.f16x2 %1, %3, %4, t; }"
        : "=&r"(r.re), "=r"(r.im) : "r"(a.re), "r"(a.im), "r"(m.re), "r"(m.im));
    return r;
}

struct KParams { uint32_t v[6], logdt, dskip; };
__device__ __forceinline__ KParams kload(const Params& p, int ch, int half) {
    KParams k;
    const int o = ch * NST + 64 * half + 2 * (threadIdx.x & 31);
    const __nv_bfloat16* a[8] = {p.Are + o, p.Aim + o, p.Bre + o, p.Bim + o, p.Cre + o, p.Cim + o, p.logdt + ch, p.Dskip + ch};
#pragma unroll
    for (int i = 0; i < 6; i++) k.v[i] = ldg32(a[i]);
    k.logdt = ldg16(a[6]);
    k.dskip = ldg16(a[7]);
    return k;
}

__device__ __forceinline__ void kgen(const KParams& k, uint32_t stage, float (&kv)[21], float& fin, uint32_t sb) {
    const int lane = threadIdx.x & 31, mi = lane >> 3, r8 = lane & 7;
    const uint32_t (&v)[6] = k.v;
    const uint32_t w2 = stage + (lane & 15) * 16, w1 = stage + lane * 4;
    auto put = [&](int row, h2c x) { stsm2(w2 + row * KG_ROW, x.re, x.im); };
    auto keep = [&](int row, h2c x) { sts32(w1 + row * KG_ROW, x.re); sts32(w1 + row * KG_ROW + 128, x.im); };
    sts32(w1, 0x3c003c00u); sts32(w1 + 128, 0u);
    const float dt = rbf(ex2(bf_lo(k.logdt) * 1.4426950408889634f));
    const float dl = dt * 1.4426950408889634f;
    const float xa = bf_lo(v[0]) * dl, xb = bf_hi(v[0]) * dl, ya = bf_lo(v[1]) * dt, yb = bf_hi(v[1]) * dt;
    cplx a = cexp2(xa, ya), b = cexp2(xb, yb), c = cexp2(64.f * xa, 64.f * ya), d = cexp2(64.f * xb, 64.f * yb);
    cplx Wa, Wb;
    Wa.re = bf_lo(v[4]) * bf_lo(v[2]) - bf_lo(v[5]) * bf_lo(v[3]); Wa.im = bf_lo(v[4]) * bf_lo(v[3]) + bf_lo(v[5]) * bf_lo(v[2]);
    Wb.re = bf_hi(v[4]) * bf_hi(v[2]) - bf_hi(v[5]) * bf_hi(v[3]); Wb.im = bf_hi(v[4]) * bf_hi(v[3]) + bf_hi(v[5]) * bf_hi(v[2]);
    const float mx = fmaxf(fmaxf(fabsf(Wa.re), fabsf(Wa.im)), fmaxf(fabsf(Wb.re), fabsf(Wb.im)));
    const uint32_t ex = max(__reduce_max_sync(0xffffffffu, __float_as_uint(mx)) >> 23, 10u);
    const float sc = __uint_as_float((263u - ex) << 23);
    fin = dt * __uint_as_float((ex - 9u) << 23);
    Wa.re *= sc; Wa.im *= sc; Wb.re *= sc; Wb.im *= sc;
    kv[16] = (float)__reduce_add_sync(0xffffffffu, __float2int_rn((Wa.re + Wb.re) * 32768.f)) * (1.f / 32768.f);
    h2c c1;
    {
        cplx p, q;
        p.re = Wa.re * a.re - Wa.im * a.im; p.im = -(Wa.re * a.im) - Wa.im * a.re; q.re = Wb.re * b.re - Wb.im * b.im; q.im = -(Wb.re * b.im) - Wb.im * b.re;
        c1 = hpack(p, q);
    }
    const h2c z1 = hpack(a, b); a = csq(a); b = csq(b);
    const h2c z64 = hpack(c, d); c = csq(c); d = csq(d);
    const h2c z2 = hpack(a, b); a = csq(a); b = csq(b);
    const h2c z128 = hpack(c, d); c = csq(c); d = csq(d);
    const h2c z4 = hpack(a, b); a = csq(a); b = csq(b);
    const h2c z256 = hpack(c, d); c = csq(c); d = csq(d);
    const h2c z8 = hpack(a, b); a = csq(a); b = csq(b);
    const h2c z512 = hpack(c, d);
    const h2c z16 = hpack(a, b); a = csq(a); b = csq(b);
    const h2c z32 = hpack(a, b);
    keep(32, z64);
    const h2c c2 = hmulj(c1, z1), c3 = hmulj(c1, z2), c4 = hmulj(c2, z2), c6 = hmulj(c2, z4), c8 = hmulj(c4, z4);
    keep(8, c1); keep(9, c2); keep(10, c3); keep(11, c4); put(12, hmulj(c1, z4)); keep(13, c6); put(14, hmulj(c3, z4)); keep(15, c8);
    const h2c e260 = hmulj(c4, z256), e264 = hmulj(c8, z256), e776 = hmulj(e264, z512), e840 = hmulj(e776, z64);
    put(16, hmulj(c2, z256)); put(17, hmulj(c4, z512)); keep(18, e260); put(19, hmulj(c8, z512)); put(20, hmulj(c6, z256)); put(21, hmulj(e260, z512)); keep(22, e264); keep(23, e776);
    const h2c z24 = hmulc(z8, z16);
    keep(1, z8); keep(2, z16); keep(3, z24); keep(4, z32); put(5, hmulc(z8, z32)); put(6, hmulc(z16, z32)); put(7, hmulc(z24, z32));
    const h2c d0 = hmulj(e840, z128), d1 = hmulj(e840, z256), d3 = hmulj(e840, z512), d2 = hmulj(d0, z256);
    keep(24, d0); keep(25, d1); keep(27, d3); keep(26, d2); put(28, hmulj(d0, z512)); put(29, hmulj(d1, z512)); put(31, hmulj(d3, z512)); put(30, hmulj(d2, z512));
    __syncwarp();
    const uint32_t ra = stage + ((mi & 1) ? 32 : r8) * KG_ROW + (mi >> 1) * 128, rb = stage + (8 + r8) * KG_ROW + (mi & 1) * 128 + (mi >> 1) * 16;
    float acc[5][4];
#pragma unroll
    for (int i = 0; i < 5; i++) acc[i][0] = acc[i][1] = acc[i][2] = acc[i][3] = 0.f;
#pragma unroll
    for (int s = 0; s < 4; s++) {
        uint32_t A[2][4], B[3][4];
        ldsm4(A[0], ra + 32 * s); ldsm4(A[1], ra + 32 * s + 16);
        ldsm4(B[0], rb + 32 * s); ldsm4(B[1], rb + 32 * s + 8 * KG_ROW); ldsm4(B[2], rb + 32 * s + 16 * KG_ROW);
#pragma unroll
        for (int e = 0; e < 2; e++) {
            const h2c p0 = {A[e][0], A[e][2]}, m = {A[e][1], A[e][3]};
            const h2c p1 = hmulc(p0, m), p2 = hmulc(p1, m), p3 = hmulc(p2, m);
            mma_f16(acc[1], p1.re, p2.re, p1.im, p2.im, B[0][2 * e], B[0][2 * e + 1]);
            mma_f16(acc[3], p1.re, p2.re, p1.im, p2.im, B[1][2 * e], B[1][2 * e + 1]);
            mma_f16(acc[4], p1.re, p2.re, p1.im, p2.im, B[2][2 * e], B[2][2 * e + 1]);
            mma_f16(acc[0], p0.re, p3.re, p0.im, p3.im, B[0][2 * e], B[0][2 * e + 1]);
            mma_f16(acc[2], p0.re, p3.re, p0.im, p3.im, B[1][2 * e], B[1][2 * e + 1]);
        }
    }
#pragma unroll
    for (int q = 0; q < 4; q++) {
        const int i = (q == 1 || q == 2), h = 2 * (q >> 1);
        kv[2 * q] = acc[i][h]; kv[2 * q + 1] = acc[i][h + 1]; kv[8 + q] = acc[2 + i][h]; kv[12 + q] = acc[2 + i][h + 1]; kv[17 + q] = acc[4][2 * (q & 1) + (q >> 1)];
    }
}
__device__ __forceinline__ void ksend(const float (&kv)[21], float fin, uint32_t mine, bool second) {
    const uint32_t lo = (threadIdx.x & 31) * 16;
    auto send = [&](int i, int k) { sts128(mine + lo + 512 * i, __float_as_uint(kv[k] * fin), __float_as_uint(kv[k + 1] * fin), __float_as_uint(kv[k + 2] * fin), __float_as_uint(kv[k + 3] * fin)); };
    __syncwarp();
    if (second) send(0, 17);
    else { send(0, 0); send(1, 4); send(2, 8); send(3, 12); sts32(mine + 2048, __float_as_uint(kv[16] * fin)); }
}
__device__ __forceinline__ void krecv(float (&kv)[21], float fin, uint32_t other, int i, int k) {
    const uint4 x = lds128(other + (threadIdx.x & 31) * 16 + 512 * i);
    kv[k] = kv[k] * fin + __uint_as_float(x.x); kv[k + 1] = kv[k + 1] * fin + __uint_as_float(x.y); kv[k + 2] = kv[k + 2] * fin + __uint_as_float(x.z); kv[k + 3] = kv[k + 3] * fin + __uint_as_float(x.w);
}

__device__ __forceinline__ void kwords(float (&kv)[21], uint32_t (&w)[21]) {
    const int lane = threadIdx.x & 31, t = lane & 3;
    w[20] = pack_bf16(__shfl_sync(0xffffffffu, kv[11], 31), 0.f);
    const float k512 = bf_lo(w[20]);
    if (lane >= 30) kv[11] = lane == 31 ? 0.f : kv[11] - k512;
    float carry = kv[16];
#pragma unroll
    for (int q = 0; q < 8; q++) {
        const float hi = q < 4 ? kv[2 * q + 1] : kv[4 + q];
        const float sh = __shfl_sync(0xffffffffu, hi, (lane + 31) & 31);
        const float prev = lane ? sh : carry;
        carry = sh;
        const float lo = q < 4 ? kv[2 * q] : ((lane & 1) ? hi : prev);
        w[2 * q] = pack_bf16(lo, prev); w[2 * q + 1] = pack_bf16(hi, lo);
    }
    const float up = __shfl_up_sync(0xffffffffu, kv[15], 2);
    w[16] = pack_bf16(kv[12], t >= 2 ? up : lane == 29 ? k512 : 0.f);
#pragma unroll
    for (int q = 1; q < 4; q++) w[16 + q] = pack_bf16(kv[12 + q], kv[11 + q]);
}
__device__ __forceinline__ void kstore(const uint32_t (&w)[21], uint32_t kt) {
    const int lane = threadIdx.x & 31, g = lane >> 2, t = lane & 3;
    if (lane == 0) sts32(kt + KT_P + 15 * 4, w[0] >> 16);
#pragma unroll
    for (int q = 0; q < 8; q++) sts64(kt + KT_P + (64 * q + 16) * 4 + lane * 8, w[2 * q], w[2 * q + 1]);
    const uint32_t a4 = kt + KT_P4 + (13 + 2 * g + (t & 1) + 64 * (t >> 1)) * 4;
#pragma unroll
    for (int q = 0; q < 4; q++) sts32(a4 + 64 * q, w[16 + q]);
    sts32(t >= 2 ? a4 + 256 : kt + KT_P4 + 12 * 4, __byte_perm(w[19], w[20], t >= 2 ? 0x1077 : 0x7754));
}
__device__ __forceinline__ uint4 kwords8(const float (&kv)[21]) {
    const float up = __shfl_up_sync(0xffffffffu, kv[20], 1);
    return make_uint4(pack_bf16(kv[17], (threadIdx.x & 3) ? up : 0.f), pack_bf16(kv[18], kv[17]), pack_bf16(kv[19], kv[18]), pack_bf16(kv[20], kv[19]));
}

__device__ __forceinline__ uint32_t band(int e, int c, int h) {
    return (((unsigned)(e - c + h) <= 2u * h) ? 0x3f80u : 0u) | (((unsigned)(e + 1 - c + h) <= 2u * h) ? 0x3f800000u : 0u);
}

__device__ __forceinline__ void conv_consts(uint32_t sb, int rank) {
    const int lane = threadIdx.x & 31, g = lane >> 2, t = lane & 3, mi = lane >> 3, r8 = lane & 7, d0 = g - 2 * t, pg = (g >> 1) + 4 * (g & 1);
    const uint32_t a = sb + SC_CT + lane * 16;
    sts128(a, band(4 * t, 4 + g, 4), band(4 * t, 4 + g, 3), band(4 * t + 2, 4 + g, 4), band(4 * t + 2, 4 + g, 3));
    sts128(a + 512, pg * 16 + (t == 0 ? UT_PL - 8 : t == 3 ? UT_PL : 8 * (t - 1)), pg * 16 + (t == 0 ? -8 : t == 3 ? 0 : UT_PL - 16 + 8 * (t - 1)),
           (mi & 1) * UT_PL + (mi >> 1) * 128 + r8 * 16, KT_P + (15 + d0) * 4);
    sts128(a + 1024, (((unsigned)(d0 - 3) < 2u) ? 0xffffu : 0u) | (((unsigned)(d0 - 4) < 2u) ? 0xffff0000u : 0u),
           (((unsigned)(d0 + 5) < 2u) ? 0xffffu : 0u) | (((unsigned)(d0 + 4) < 2u) ? 0xffff0000u : 0u), KT_P4 + (3 + g - t) * 16, UT_PL - 16 + lane * 16);
    sts128(a + 1536, band(2 * t, 6 + g, 2), band(2 * t, 2 + g, 1), band(2 * t + 8, 6 + g, 2), band(2 * t + 8, 2 + g, 1));
    sts128(a + 2048, pg * 16 + (t == 3 ? UT_PL : 4 + 4 * t), pg * 16 + (t == 3 ? 16 : UT_PL + 4 + 4 * t),
           mapa(sb + SC_OUT + rank * OUT_HALF + g * 32 + (t & 1) * 16, t >> 1), mapa(sb + SB_OUT, t >> 1));
}

__device__ __forceinline__ void conv_windows(uint32_t sb, int warp, uint32_t (&q)[8][4]) {
    const uint32_t ut = sb + SC_UT + warp * UT_STRIDE + 128, ct = sb + SC_CT + (threadIdx.x & 31) * 16;
    const uint2 c1 = lds64(ct + 512);
    const uint4 c0 = lds128(ct);
    const uint32_t w0 = c0.x, w1 = c0.y, w2 = c0.z, w3 = c0.w, a0 = ut + c1.x, a1 = ut + c1.y;
#pragma unroll
    for (int j = 0; j < 8; j++) {
        const uint2 x = lds64(a0 + 128 * j - 16), y = lds64(a1 + 128 * j), z = lds64(a0 + 128 * j);
        float X[4], Y[4], Z[4];
        mma_bf0(X, w0, w1, w2, w3, x.x, x.y); mma_bf0(Y, w0, w1, w2, w3, y.x, y.y); mma_bf0(Z, w0, w1, w2, w3, z.x, z.y);
        q[j][0] = pack_bf16(Y[2], Y[3]); q[j][1] = pack_bf16(Z[2], Z[3]); q[j][2] = pack_bf16(X[0], X[1]); q[j][3] = pack_bf16(Y[0], Y[1]);
    }
}
__device__ __forceinline__ uint4 conv_fetch(const Params& p, uint32_t sb, int cb, int warp, uint32_t t0) {
    mbar_wait(sb + SB_UT + 8);
    const uint32_t tag = lds32(sb + SC_TAG) << 16;
    const uint4* src = p.scr->kx + (4 * cb + warp - 4) * 192 + (threadIdx.x & 31);
    while (clk() - t0 < KDELAY) __nanosleep(KSLEEP);
    uint4 x[5], k8;
    for (int it = 0;;) {
#pragma unroll
        for (int i = 0; i < 5; i++) x[i] = ld_pkt(src + 32 * i);
        k8 = ld_pkt(src + 160);
        if (__all_sync(0xffffffffu, ((x[0].w ^ tag) | (x[1].w ^ tag) | (x[2].w ^ tag) | (x[3].w ^ tag) | (x[4].w ^ tag) | (k8.w ^ tag)) < 0x10000u)) break;
        POLL_GUARD(it);
    }
    uint32_t w[21];
#pragma unroll
    for (int i = 0; i < 4; i++) { w[4 * i] = x[i].x; w[4 * i + 1] = x[i].y; w[4 * i + 2] = x[i].z; w[4 * i + 3] = __byte_perm(x[i].w, x[i].z, 0x5410); }
    w[16] = x[4].x; w[17] = __byte_perm(x[4].y, x[4].x, 0x5432); w[18] = x[4].y; w[19] = x[4].z; w[20] = x[4].w;
    kstore(w, sb + SC_KT + warp * KT_BYTES);
    k8.w = __byte_perm(k8.w, k8.z, 0x5410);
    return k8;
}

__device__ __forceinline__ void conv_warp(uint32_t sb, int warp, const uint32_t (&q)[8][4], uint4 k8) {
    const int lane = threadIdx.x & 31;
    const uint32_t kt = sb + SC_KT + warp * KT_BYTES, ut = sb + SC_UT + warp * UT_STRIDE + 128, ct = sb + SC_CT + lane * 16;
    float acc[16][4];
    const uint32_t oz = blockIdx.y;
    const uint2 c1 = lds64(ct + 520);
    {
        const uint32_t a8 = kt + KT_P8 + (6 + 32 * (lane & 3) + (lane >> 2)) * 4;
        sts32(a8, k8.x); sts32(a8 + 32, k8.y); sts32(a8 + 64, k8.z); sts32(a8 + 96, k8.w);
        __syncwarp();
#pragma unroll
        for (int l = 0; l < 8; l++) {
            const uint2 kb = lds64(kt + KT_P8 + (3 + 8 * l + (lane >> 2) - (lane & 3)) * 8);
#pragma unroll
            for (int j = 0; j < 8 - l; j++) {
                if (l == 0) mma_bf0(acc[8 + j], q[j][0], q[j][1], q[j][2], q[j][3], kb.x, kb.y);
                else mma_bf(acc[8 + j + l], q[j][0], q[j][1], q[j][2], q[j][3], kb.x, kb.y);
            }
        }
    }
    asm volatile("setmaxnreg.inc.sync.aligned.u32 168;");
    if (warp < 4) { bar_sync(6 + warp, 64); mbar_wait(sb + SB_UT + 8); }
    uint4 c2;
    {
        uint32_t a[4][4], b[8][4];
        uint32_t k1 = kt + c1.y, u1 = ut + c1.x;
        auto lda = [&](int j1) { a[j1][0] = lds32(k1 + 512 * j1); a[j1][1] = lds32(k1 + 512 * j1 + 32); a[j1][2] = lds32v(k1 + 512 * j1 - 32); a[j1][3] = DUPA; };
        lda(0);
#pragma unroll
        for (int m2 = 0; m2 < 8; m2++) ldsm4(b[m2], u1 + 256 * m2);
#pragma unroll
        for (int i = 0; i < 8; i++) acc[i][0] = acc[i][1] = acc[i][2] = acc[i][3] = 0.f;
#pragma unroll DUNR
        for (int j0 = 0; j0 < 8; j0++) {
            k1 += 64; u1 -= 16;
            lda(3);
#pragma unroll
            for (int m = 0; m < 16; m++) {
                mma_bf(acc[m], a[0][0], a[0][1], a[0][2], a[0][3], b[m >> 1][2 * (m & 1)], b[m >> 1][2 * (m & 1) + 1]);
                if (m & 1) ldsm4(b[m >> 1], u1 + 256 * (m >> 1));
            }
            lda(2); lda(1); lda(0);
#pragma unroll
            for (int j1 = 3; j1 > 0; j1--)
#pragma unroll
                for (int m = 0; m + j1 < 16; m++) mma_bf(acc[m + j1], a[j1][0], a[j1][1], a[j1][2], a[j1][3], b[m >> 1][2 * (m & 1)], b[m >> 1][2 * (m & 1) + 1]);
        }
        c2 = lds128(ct + 1024);
        const uint32_t kv = __byte_perm(lds32(kt + KT_P4 + 140 * 4), 0, 0x1010), e0 = kv & c2.x, e1 = kv & c2.y;
        const uint32_t e3 = e0 + oz, e4 = e1 + oz, z2 = oz + oz;
        uint32_t f[2][4];
        ldsm4(f[0], ut + c2.w); ldsm4(f[1], ut + c2.w + 512);
#pragma unroll
        for (int m = 1; m < 16; m++) mma_bf(acc[m], a[0][0], a[0][1], a[0][2], a[0][3], b[m >> 1][2 * (m & 1)], b[m >> 1][2 * (m & 1) + 1]);
#pragma unroll
        for (int m = 1; m < 9; m++) mma_bf(acc[m + 7], e0, e1, oz, e3, b[m >> 1][2 * (m & 1)], b[m >> 1][2 * (m & 1) + 1]);
#pragma unroll
        for (int m = 0; m < 8; m++) mma_bf8(acc[m + 8], e4, z2, f[m >> 2][m & 3]);
    }
    uint32_t kb[5][4];
#pragma unroll
    for (int l = 0; l < 5; l++) { const uint4 x = lds128(kt + c2.z + 128 * l); kb[l][0] = x.x; kb[l][1] = x.y; kb[l][2] = x.z; kb[l][3] = x.w; }
    const uint4 c3 = lds128(ct + 1536), c4 = lds128(ct + 2048);
    const uint32_t w0 = c3.x, w1 = c3.y, w2 = c3.z, w3 = c3.w, a0 = ut + c4.x, a1 = ut + c4.y, od = c4.z + warp * 288, ob = c4.w;
    auto emit = [&](int q) {
        st_async128(od + q * OUT_STAGE, pack_bf16(acc[2 * q][0], acc[2 * q][1]), pack_bf16(acc[2 * q][2], acc[2 * q][3]),
                    pack_bf16(acc[2 * q + 1][0], acc[2 * q + 1][1]), pack_bf16(acc[2 * q + 1][2], acc[2 * q + 1][3]), ob + 8 * q);
    };
    uint32_t x[12][4];
    auto load = [&](int j) { x[j][0] = lds32(a0 + 128 * j - 16); x[j][1] = lds32(a1 + 128 * j - 16); x[j][2] = lds32(a0 + 128 * j); x[j][3] = lds32(a1 + 128 * j); };
    {
        float Z[4] = {0.f, 0.f, 0.f, 0.f};
        mma_bf8(Z, w2, w3, lds32(a1 - 128));
        const uint32_t z5 = pack_bf16(Z[0], Z[1]);
#pragma unroll
        for (int l = 0; l < 5; l++) mma_bf8(acc[3 + l], oz * 3, z5, kb[l][0]);
    }
    load(0); load(1);
    emit(0); emit(1);
#pragma unroll
    for (int j = 0; j < 12; j++) {
        if (j == JBAR) bar_sync(2 + (warp & 3), 64);
        if (j + 2 < 11) load(j + 2);
        if (j == 10) load(11);
        float X[4], Y[4], Z[4];
        mma_bf0(X, w0, w1, w2, w3, x[j][0], x[j][1]); mma_bf0(Y, w0, w1, w2, w3, x[j][1] + oz, x[j][2] + oz); mma_bf0(Z, w0, w1, w2, w3, x[j][2], x[j][3]);
        const uint32_t x5 = pack_bf16(X[0], X[1]), x3 = pack_bf16(X[2], X[3]), y5 = pack_bf16(Y[0], Y[1]), y3 = pack_bf16(Y[2], Y[3]), z5 = pack_bf16(Z[0], Z[1]), z3 = pack_bf16(Z[2], Z[3]);
        const uint32_t y3c = y3 + oz, y5c = y5 + oz;
#pragma unroll
        for (int l = 0; l < 5; l++) if (j + 4 + l < 16) mma_bf(acc[j + 4 + l], y5, z5, y3, z3, kb[l][0], kb[l][1]);
#pragma unroll
        for (int l = 0; l < 5; l++) if (j + 4 + l < 16) mma_bf(acc[j + 4 + l], x5, y5c, x3, y3c, kb[l][2], kb[l][3]);
        if (j & 1) emit(2 + (j >> 1));
    }
}

__device__ __forceinline__ uint32_t utile_addr(uint32_t sb, int row, int c8) {
    return sb + SC_UTILE + (row >> 9) * 8192 + (((row >> 4) & 3) + 4 * (row & 1) + 8 * ((row >> 7) & 3) + 32 * ((row >> 1) & 7)) * 32 + ((c8 ^ row) & 1) * 16;
}

__device__ __forceinline__ void conv_helper(const Params& p, const CUtensorMap* mU, uint32_t sb, int cb, int hw, uint32_t t0) {
    const int lane = threadIdx.x & 31, g = lane >> 2, t = lane & 3, mi = lane >> 3, r8 = lane & 7;
    const int rank = cb & 1, slab = cb >> 1;
    const uint32_t bar_out = sb + SB_OUT, s_key = sb + SC_KEY;
    asm volatile("setmaxnreg.dec.sync.aligned.u32 88;");
    uint32_t tag = 0;
    if (lane == 0) {
        const uint32_t b = sb + SC_BAR + 8 * hw;
        mbar_init(b, hw < 4 ? 1 : 9); mbar_init(bar_out + 8 * hw, 1);
        mbar_fence_init();
        if (hw < 6) mbar_expect(b, 8192);
        if (hw < 4) {
            spin_until(t0, hw < 2 ? UDELAY : VDELAY);
            tma5d(sb + SC_UTILE + hw * 8192, mU, 16 * slab, 4 * rank, 0, 4 * hw, 0, b);
        }
        mbar_expect(bar_out + 8 * hw, 4096);
        if (hw == 4) tag = take_ticket(&p.scr->launch);
    }
    __syncwarp();
    cluster_arrive_relaxed();
    if (lane < 16) sts128(sb + SC_UT + hw * UT_STRIDE + mi * UT_PL + r8 * 16, 0, 0, 0, 0);
    if (lane < 17) sts128(sb + SC_KT + hw * KT_BYTES + 16 * (lane < 4 ? lane : lane < 11 ? 128 + lane : 164 + lane), 0, 0, 0, 0);
    if (hw == 7) conv_consts(sb, rank);
    if (hw == 4) { tag = tag_of(__shfl_sync(0xffffffffu, tag, 0)); sts32(sb + SC_TAG, tag); }
    cluster_wait();
    {
        const int box = hw >> 2, h = hw & 1, k0 = hw & 2;
        const uint32_t src = sb + SC_UTILE + box * 8192 + h * 4096 + k0 * 256 + (32 * mi + (r8 >> 1) + 4 * (r8 & 1)) * 32;
        const uint32_t so = ((rank ^ r8) & 1) << 4;
        const uint32_t dst = sb + SC_UT + g * UT_STRIDE + 128 + h * UT_PL + k0 * 128 + (32 * box + 4 * rank + t) * 16;
        const uint32_t rdst = mapa(dst, rank ^ 1), rbar = mapa(sb + SB_UT, rank ^ 1);
#pragma unroll 1
        for (int i = 0; i < 2; i++) {
            mbar_wait(sb + SC_BAR + 8 * box + 16 * i);
            while (clk() - t0 < TDELAY + i * TSTEP) __nanosleep(40);
            const uint32_t ts = clk();
            uint32_t a[2][4], b[2][4];
#pragma unroll
            for (int k = 0; k < 2; k++) { ldsm4t(a[k], src + (so ^ 16) + k * 256 + i * 16384); ldsm4t(b[k], src + so + k * 256 + i * 16384); }
#pragma unroll
            for (int k = 0; k < 2; k++) sts128(dst + k * 128 + i * 1024, b[k][0], b[k][1], b[k][2], b[k][3]);
#pragma unroll
            for (int k = 0; k < 2; k++) {
                if (k == 0) { __syncwarp(); if (lane == 0) mbar_arrive(sb + SB_UT + 8 * i); }
                spin_until(ts, (hw + 8 * k) * PACE);
                st_async128(rdst + k * 128 + i * 1024, a[k][0], a[k][1], a[k][2], a[k][3], rbar + 8 * i);
            }
        }
    }
    if (hw > 4) { bar_arrive(1, 256); return; }
    if (hw == 4) {
        uint32_t key;
        for (int it = 0;;) {
            key = ld_rlx32(&p.scr->sel[g]);
            if (__all_sync(0xffffffffu, ((key >> 11) & 3u) == tag)) break;
            POLL_GUARD(it);
            __nanosleep(200);
        }
        if (lane == 31) sts32(s_key, key);
        bar_arrive(1, 256);
        const int row = key_row(key);
        const bool own = ((row >> 6) & 1) == rank;
        uint32_t* const op = (uint32_t*)(p.out + row * DM + 16 * slab) + 2 * t;
        if (own) asm volatile("st.relaxed.gpu.global.v2.b32 [%0], {%1, %1};" :: "l"(op), "r"(0) : "memory");
        uint32_t rc;
        for (int it = 0;;) { rc = ld_rlx32(&p.scr->rec[row]); if (((rc >> 14) & 3u) == tag) break; POLL_GUARD(it); }
        __syncwarp();
        asm volatile("fence.acq_rel.gpu;" ::: "memory");
        if (lane < 8) st_rlx32(&p.scr->zero[8 * cb + lane], tag);
        if (own) {
            const uint32_t gg = __byte_perm(rc, 0, 0x1010) & 0x3fff3fffu;
            const uint32_t ya = sb + SC_OUT + (row >> 8) * OUT_STAGE + (t >> 1) * OUT_HALF + (t & 1) * 1152 + (row & 7) * 32 + ((row >> 5) & 1) * 16
                                + ((row >> 7) & 1) * 8 + ((row >> 3) & 1) * 4 + ((row >> 4) & 1) * 2;
            mbar_wait(bar_out + 8 * (row >> 8));
            const uint32_t y0 = lds16(ya) | (lds16(ya + 288) << 16), y1 = lds16(ya + 576) | (lds16(ya + 864) << 16);
            red_bf2(op, hmul2(gg, y0)); red_bf2(op + 1, hmul2(gg, y1));
        }
        return;
    }
    bar_sync(1, 256);
    {
        const uint32_t last = lds32(s_key), tg = ((last >> 11) & 3u) << 14;
        const int par = hw >> 1, i0 = 4 * (hw & 1);
        const int row0 = 256 * par + 128 * (g >> 2) + 64 * rank + 32 * (t >> 1) + 16 * (g & 1) + 8 * ((g >> 1) & 1) + i0;
        uint4 r[4];
        for (int it = 0;;) {
            uint32_t bad = 0;
#pragma unroll
            for (int k = 0; k < 4; k++) { r[k] = ld_rlx128(&p.scr->rec[row0 + 512 * k]); }
#pragma unroll
            for (int k = 0; k < 4; k++) bad |= (r[k].x ^ tg) | (r[k].y ^ tg) | (r[k].z ^ tg) | (r[k].w ^ tg);
            if ((bad & 0xc000u) == 0) break;
            POLL_GUARD(it);
        }
        const uint32_t thr = last & ~0x1800u;
        const uint32_t ya = sb + SC_OUT + par * OUT_STAGE + ((r8 >> 1) & 1) * OUT_HALF + (2 * mi + (r8 & 1)) * 288 + (2 * i0 + (r8 >> 2)) * 16;
        const uint32_t ua = utile_addr(sb, row0, t & 1);
        __nv_bfloat16* op = p.out + row0 * DM + 16 * slab + 8 * (t & 1);
#pragma unroll
        for (int k = 0; k < 4; k++) {
            const uint32_t rr[4] = {r[k].x, r[k].y, r[k].z, r[k].w};
            uint4 ou[4];
            uint32_t gg[4];
#pragma unroll
            for (int i = 0; i < 4; i++) {
                gg[i] = __byte_perm(rr[i], 0, 0x1010) & 0x3fff3fffu;
                const uint32_t om = hsub2(0x3f803f80u, gg[i]);
                const uint4 u4 = lds128((ua ^ ((i & 1) * 16)) + k * 8192 + (i & 1) * 128 + (i >> 1) * 1024);
                ou[i] = make_uint4(hmul2(om, u4.x), hmul2(om, u4.y), hmul2(om, u4.z), hmul2(om, u4.w));
            }
            mbar_wait(bar_out + 8 * par + 16 * k);
            uint32_t y[4][4];
#pragma unroll
            for (int i = 0; i < 4; i++) ldsm4t(y[i], ya + 2 * k * OUT_STAGE + 32 * i);
#pragma unroll
            for (int i = 0; i < 4; i++) {
                const uint4 o = make_uint4(hfma2(gg[i], y[i][0], ou[i].x), hfma2(gg[i], y[i][1], ou[i].y), hfma2(gg[i], y[i][2], ou[i].z), hfma2(gg[i], y[i][3], ou[i].w));
                if (((rr[i] & 0xffff0000u) | (uint32_t)(2047 - 512 * k - i - row0)) < thr) *(uint4*)(op + (512 * k + i) * DM) = o;
            }
        }
    }
}

__device__ __forceinline__ void ffn_cta(const Params& p, const CUtensorMap* mR, const CUtensorMap* mG64, const CUtensorMap* mU64, const CUtensorMap* mG16,
                                        const CUtensorMap* mU16, const CUtensorMap* mWd, uint32_t sb, int f, int warp, uint32_t t0, const uint32_t (&kw)[21], uint4 k8, int ci) {
    const int tid = threadIdx.x, lane = tid & 31, g = lane >> 2, t = lane & 3, mi = lane >> 3, r8 = lane & 7;
    const bool wide = f < 48;
    const int nunit = wide ? 10 : 8;
    const uint32_t bar_w = sb + SF_BAR, bar_d = bar_w + 72, bar_r = bar_w + 112, bar_sel = bar_w + 152, bar_free = bar_w + 160, bar_kg = bar_w + 184, bar_tk = bar_w + 192;
    uint32_t tag;
    uint2* const pdst = p.scr->part + (3 * warp * NFFN + f) * 32 + lane;
    auto clear_part = [&]() { if (CLR == 1) { st_pkt8(pdst, 0, 0); st_pkt8(pdst + NFFN * 32, 0, 0); st_pkt8(pdst + 2 * NFFN * 32, 0, 0); } };
    if (warp == 13) {
        if (lane == 0) {
#pragma unroll
            for (int i = 0; i < 14; i++) mbar_init(bar_w + 8 * i, 1);
            mbar_init(bar_sel, f >= 44 ? 5 : 4); mbar_init(bar_free, nunit); mbar_init(bar_free + 8, nunit); mbar_init(bar_free + 16, nunit); mbar_init(bar_kg, nunit); mbar_init(bar_tk, 1);
            mbar_fence_init();
        }
        __syncwarp();
        cluster_arrive_relaxed();
        if (lane == 0) {
            spin_until(t0, FDELAY);
            prefetch_map(mG64); prefetch_map(mU64); prefetch_map(mG16); prefetch_map(mU16); prefetch_map(mWd);
            spin_until(t0, WDELAY);
#pragma unroll 1
            for (int n = 0; n < 9; n++) {
                if (n >= WWIN) { int it = 0; while (!mbar_test(bar_w + 8 * (n - WWIN)) && !mbar_test(bar_free)) { SPIN; POLL_GUARD(it); } }
                if (n == 4) {
                    uint32_t tn = clk() - PFP;
                    for (int pf = 4, it = 0; !mbar_test(bar_kg);) {
                        if (pf < PFN && clk() - tn >= PFP) {
                            pf2d(mG64, 64 * f, 64 * pf); pf2d(mU64, 64 * f, 64 * pf);
                            if (wide) { pf2d(mG16, 3840 + 16 * f, 64 * pf); pf2d(mU16, 3840 + 16 * f, 64 * pf); }
                            pf++; tn += PFP;
                        }
                        POLL_GUARD(it);
                    }
                }
                if (n == 8) mbar_wait(bar_sel);
                const uint32_t b = bar_w + 8 * n, d = sb + n * PIECE;
                mbar_expect(b, wide ? PIECE : 16384);
                tma2d(d, mG64, 64 * f, 64 * n, b); tma2d(d + 8192, mU64, 64 * f, 64 * n, b);
                if (wide) { tma2d(d + 16384, mG16, 3840 + 16 * f, 64 * n, b); tma2d(d + 18432, mU16, 3840 + 16 * f, 64 * n, b); }
            }
#pragma unroll 1
            for (int i = 0; i < nunit / 2; i++) {
                if (i < 2) { int it = 0; while (!mbar_test(bar_w + 8 * (9 + i - WWIN)) && !mbar_test(bar_free)) { SPIN; POLL_GUARD(it); } }
                else mbar_wait(bar_free + 8 * (i - 2));
                mbar_expect(bar_d + 8 * i, 18432);
                tma2d(i < 2 ? sb + SF_R + i * 18432 : sb + (i - 2) * PIECE, mWd, 0, 9 * (i < 4 ? 64 * f + 16 * i : 3840 + 16 * f), bar_d + 8 * i);
            }
        }
        return;
    }
    if (warp >= 10) {
        const int ng = f >= 44 ? 5 : 4, r0 = f >= 44 ? 1408 + 40 * (f - 44) : 32 * f;
        const int grp = warp == 12 ? 4 : warp < 12 ? warp - 10 : warp - 12;
        const uint32_t rows = grp < 4 ? sb + SF_R + grp * 9216 : sb + SF_R4;
        const int i = 32 * grp + lane;
        if (lane == 0) { mbar_init(bar_r + 8 * grp, 1); mbar_fence_init(); mbar_expect(bar_r + 8 * grp, 9216); }
        __syncwarp();
        cluster_arrive_relaxed();
        if (grp == 4) {
#pragma unroll 1
            for (int k = lane; k < 256; k += 32) sts128(sb + SF_LIST + k * 16, 0, 0, 0, 0);
        }
        uint4 w;
        spin_until(t0, RDELAY);
        if (lane == 0 && grp < ng) tma2d(rows, mR, 0, 9 * (r0 + 8 * grp), bar_r + 8 * grp);
        if (i < 144) w = ldg128((const uint4*)(i < 72 ? p.wr : p.gatew - DM) + i);
        if (i == 159) w.x = take_ticket(&p.scr->launch);
        if (grp < ng && t == 0) st_rlx32(&p.scr->rec[r0 + 8 * grp + g], 0);
        if (i < 144) sts128(sb + SF_WR + i * 16, w.x, w.y, w.z, w.w);
        if (i == 159) sts64(sb + SF_CNT, 0, tag_of(w.x));
        cluster_wait();
        bar_sync(10, 160);
        if (i == 159) mbar_arrive(bar_tk);
        if (grp < ng) {
            uint32_t wv[9][4];
            const uint32_t wa = sb + SF_WR + ((r8 >> 1) & 1) * 1152 + (2 * mi + (r8 & 1)) * 16;
#pragma unroll
            for (int k = 0; k < 9; k++) ldsm4(wv[k], wa + 128 * k);
            tag = lds32(sb + SF_TK);
            float c[3][4];
            mbar_wait(bar_r + 8 * grp);
#pragma unroll
            for (int k = 0; k < 18; k++) {
                const int line = 9 * r8 + (k >> 1);
                uint32_t a[4];
                ldsm4(a, rows + line * 128 + ((((4 * k + mi) ^ line) & 7) << 4));
                if (k < 3) mma_bf0(c[k], a[0], a[1], a[2], a[3], wv[k >> 1][2 * (k & 1)], wv[k >> 1][2 * (k & 1) + 1]);
                else mma_bf(c[k % 3], a[0], a[1], a[2], a[3], wv[k >> 1][2 * (k & 1)], wv[k >> 1][2 * (k & 1) + 1]);
            }
            const float s = (c[0][0] + c[0][3]) + (c[1][0] + c[1][3]) + (c[2][0] + c[2][3]);
            const uint32_t gg = __shfl_down_sync(0xffffffffu, pack_bf16(sigmoidf_(rbf(s)), 0.f), 1);
            uint32_t rb = pack_bf16(0.f, s);
            rb = (rb & 0x80000000u) ? ~rb : (rb | 0x80000000u);
            if (t == 0) st_rlx32(&p.scr->rec[r0 + 8 * grp + g], (rb & 0xffff0000u) | (tag << 14) | (gg & 0x3fffu));
            if (lane == 0) { sts32(sb + SF_CLK, clk()); mbar_arrive(bar_sel); }
        }
        if (warp >= 14 && f >= 24) {
            const int ht = tid - 448, tok = ht >> 3, cp = ht & 7;
            bar_sync(8, 32 * nunit + 64);
            const uint32_t key = lds32(sb + SF_SEL + 4 * tok), x = lds32(sb + SF_XS + tok * 1168 + 32 * (f - 24) + 4 * cp);
            const int row = key_row(key);
            uint32_t rc;
            for (int it = 0;;) { rc = ld_rlx32(&p.scr->rec[row]); if (((rc >> 14) & 3u) == tag) break; POLL_GUARD(it); }
            const float om = rbf(1.f - bf_lo(rc & 0x3fffu)), rs = rbf(sigmoidf_(key_val(key)));
            bar_sync(9, 448);
            for (int it = 0; ld_acq32(&p.scr->zero[8 * (2 * (f - 24) + ((row >> 6) & 1))]) != tag;) POLL_GUARD(it);
            bar_sync(11, 448);
            float y0 = 0.f, y1 = 0.f;
#pragma unroll
            for (int k = 0; k < 12; k++) { const uint2 v = lds64(sb + SF_RED + 512 * k + (4 * tok + (cp & 3)) * 16 + (cp >> 2) * 8); y0 += __uint_as_float(v.x); y1 += __uint_as_float(v.y); }
            red_bf2((uint32_t*)(p.out + row * DM + 16 * (f - 24)) + cp, pack_bf16(om * rbf(bf_lo(x) + rbf(rbf(y0) * rs)), om * rbf(bf_hi(x) + rbf(rbf(y1) * rs))));
        }
        if (warp >= 12) return;
        clear_part();
    } else {
        if (warp >= nunit) { cluster_arrive_relaxed(); cluster_wait(); }
        mbar_wait(bar_tk);
        tag = lds32(sb + SF_TK);
        if (warp < nunit) {
            uint4* const kdst = p.scr->kx + ci * 192 + lane;
            if (warp < nunit / 2) st_pkt(kdst + 160, k8.x, k8.y, k8.z, __byte_perm(k8.w, tag, 0x5410));
            else {
#pragma unroll
                for (int i = 0; i < 4; i++) st_pkt(kdst + 32 * i, kw[4 * i], kw[4 * i + 1], kw[4 * i + 2], __byte_perm(kw[4 * i + 3], tag, 0x5410));
                st_pkt(kdst + 128, kw[16], kw[18], kw[19], __byte_perm(kw[20], tag, 0x5410));
            }
        }
        clear_part();
        if (warp < 8) {
            uint32_t k[8];
            const uint32_t tg = tag << 14;
            mbar_wait(bar_sel);
            spin_until(lds32(sb + SF_CLK), PDELAY);
            for (int it = 0;;) {
                const uint4 a = ld_rlx128(&p.scr->rec[4 * tid]), b = ld_rlx128(&p.scr->rec[1024 + 4 * tid]);
                k[0] = a.x; k[1] = a.y; k[2] = a.z; k[3] = a.w; k[4] = b.x; k[5] = b.y; k[6] = b.z; k[7] = b.w;
                if (__all_sync(0xffffffffu, (((a.x ^ tg) | (a.y ^ tg) | (a.z ^ tg) | (a.w ^ tg) | (b.x ^ tg) | (b.y ^ tg) | (b.z ^ tg) | (b.w ^ tg)) & 0xc000u) == 0)) break;
                POLL_GUARD(it);
            }
#pragma unroll
            for (int i = 0; i < 8; i++) k[i] = (k[i] & 0xffff0000u) | (uint32_t)(2047 - 1024 * (i >> 2) - (i & 3) - 4 * tid);
            const uint32_t m0 = __reduce_max_sync(0xffffffffu, max(max(k[0], k[1]), max(k[2], k[3]))), m1 = __reduce_max_sync(0xffffffffu, max(max(k[4], k[5]), max(k[6], k[7])));
            if (lane == 0) sts64(sb + SF_MAX + warp * 8, m0, m1);
            bar_sync(7, 256);
            uint32_t thr;
            {
                const uint32_t m = lds32(sb + SF_MAX + (lane & 15) * 4);
                int rk = 0;
#pragma unroll
                for (int i = 0; i < 4; i++) { const uint4 x = lds128(sb + SF_MAX + 16 * i); rk += (x.x > m) + (x.y > m) + (x.z > m) + (x.w > m); }
                thr = __reduce_max_sync(0xffffffffu, rk == 7 ? m : 0u);
            }
#pragma unroll
            for (int i = 0; i < 8; i++)
                if (k[i] >= thr) { uint32_t s; asm volatile("atom.shared.add.u32 %0, [%1], 1;" : "=r"(s) : "r"(sb + SF_CNT) : "memory"); sts32(sb + SF_LIST + 4 * s, k[i]); }
            bar_sync(7, 256);
            const int n = lds32(sb + SF_CNT);
            uint32_t key = 0;
#pragma unroll 1
            for (int base = 0; base < n; base += 32) {
                const uint32_t m = lds32(sb + SF_LIST + (base + lane) * 4);
                int rk = 0;
#pragma unroll 1
                for (int i = 0; i < n; i += 8) {
                    const uint4 x = lds128(sb + SF_LIST + 4 * i), y = lds128(sb + SF_LIST + 4 * i + 16);
                    rk += (x.x > m) + (x.y > m) + (x.z > m) + (x.w > m) + (y.x > m) + (y.y > m) + (y.z > m) + (y.w > m);
                }
                if (rk == warp && base + lane < n) key = m;
            }
            key = __reduce_max_sync(0xffffffffu, key);
            const uint4* xr = (const uint4*)(p.u + key_row(key) * DM);
            const uint4 x0 = ldg128(xr + lane), x1 = ldg128(xr + 32 + lane), x2 = ldg128(xr + 64 + r8);
            if (lane == 0) sts32(sb + SF_SEL + warp * 4, key | (tag << 11));
            bar_sync(7, 256);
            if (f == 0 && tid < 8) st_rlx32(&p.scr->sel[tid], lds32(sb + SF_SEL + tid * 4));
            const uint32_t xd = sb + SF_XS + warp * 1168 + lane * 16;
            sts128(xd, x0.x, x0.y, x0.z, x0.w); sts128(xd + 512, x1.x, x1.y, x1.z, x1.w);
            if (lane < 8) sts128(xd + 1024, x2.x, x2.y, x2.z, x2.w);
        }
        if (warp < nunit) {
            bar_sync(8, 32 * nunit + (f >= 24 ? 64 : 0));
            const int kr = 8 * (mi >> 1) + r8;
            uint32_t wa = warp < 8 ? sb + (mi & 1) * 8192 + kr * 128 + ((warp ^ r8) << 4) : sb + 16384 + (mi & 1) * 2048 + kr * 32 + (((warp ^ (r8 >> 2)) & 1) << 4);
            const uint32_t ws = warp < 8 ? 2048 : 512;
            uint32_t xa = sb + SF_XS + r8 * 1168 + mi * 16;
            float c0[4] = {0.f, 0.f, 0.f, 0.f}, c1[4] = {0.f, 0.f, 0.f, 0.f};
#pragma unroll 1
            for (int n = 0; n < 9; n++) {
                uint32_t x[2][4], a[4][4];
                ldsm4(x[0], xa); ldsm4(x[1], xa + 64);
                mbar_wait(bar_w + 8 * n);
#pragma unroll
                for (int s = 0; s < 4; s++) ldsm4t(a[s], wa + s * ws);
                mma_bf(c0, a[0][0], a[0][1], a[0][2], a[0][3], x[0][0], x[0][1]);
                mma_bf(c1, a[1][0], a[1][1], a[1][2], a[1][3], x[0][2], x[0][3]);
                mma_bf(c0, a[2][0], a[2][1], a[2][2], a[2][3], x[1][0], x[1][1]);
                mma_bf(c1, a[3][0], a[3][1], a[3][2], a[3][3], x[1][2], x[1][3]);
                if (n < 3) {
                    asm volatile("" :: "r"(a[0][0]), "r"(a[1][0]), "r"(a[2][0]), "r"(a[3][0]) : "memory");
                    __syncwarp();
                    if (lane == 0) mbar_arrive(bar_free + 8 * n);
                }
                wa += PIECE; xa += 128;
            }
            float h[2];
#pragma unroll
            for (int e = 0; e < 2; e++) {
                const float gv = rbf(c0[e] + c1[e]), uv = rbf(c0[2 + e] + c1[2 + e]);
                h[e] = rbf(gv * sigmoidf_(gv)) * uv;
            }
            uint32_t hp = pack_bf16(h[0], h[1]);
            asm volatile("movmatrix.sync.aligned.m8n8.trans.b16 %0, %0;" : "+r"(hp));
            sts32(sb + SF_H + (warp >> 1) * 256 + lane * 8 + (warp & 1) * 4, hp);
        }
    }
    bar_sync(9, f >= 24 ? 448 : 384);
    tag = lds32(sb + SF_TK);
    float d[6][4];
    uint32_t off[3];
#pragma unroll
    for (int j = 0; j < 3; j++) {
        const int tile = 3 * warp + j, line = 9 * (8 * (mi & 1) + r8) + (tile >> 2);
        off[j] = line * 128 + ((((2 * tile + (mi >> 1)) ^ line) & 7) << 4);
    }
#pragma unroll
    for (int j = 0; j < 6; j++) d[j][0] = d[j][1] = d[j][2] = d[j][3] = 0.f;
#pragma unroll 1
    for (int i = 0; i < nunit / 2; i++) {
        const uint2 hv = lds64(sb + SF_H + i * 256 + lane * 8);
        const uint32_t base = i < 2 ? sb + SF_R + i * 18432 : sb + (i - 2) * PIECE;
        mbar_wait(bar_d + 8 * i);
        uint32_t a[3][4];
#pragma unroll
        for (int j = 0; j < 3; j++) ldsm4t(a[j], base + off[j]);
#pragma unroll
        for (int j = 0; j < 3; j++) { mma_bf(d[2 * j], hv.x, 0u, hv.y, 0u, a[j][0], a[j][1]); mma_bf(d[2 * j + 1], hv.x, 0u, hv.y, 0u, a[j][2], a[j][3]); }
    }
#pragma unroll
    for (int j = 0; j < 3; j++) {
        st_pkt8(pdst + j * NFFN * 32, (pack_bf16(d[2 * j][0], d[2 * j][1]) & ~1u) | (tag & 1u), (pack_bf16(d[2 * j + 1][0], d[2 * j + 1][1]) & ~1u) | (tag >> 1));
    }
    if (f >= 24) {
        const uint2* src = p.scr->part + ((f - 24) * NFFN + 5 * warp) * 32 + lane;
        uint2 v[5];
#pragma unroll
        for (int k = 0; k < 5; k++) v[k].x = v[k].y = 0;
        for (int it = 0;;) {
#pragma unroll
            for (int k = 0; k < 5; k++) if (((v[k].x ^ tag) | (v[k].y ^ (tag >> 1))) & 1u) v[k] = ld_pkt8(src + k * 32);
            uint32_t bad = 0;
#pragma unroll
            for (int k = 0; k < 5; k++) bad |= (v[k].x ^ tag) | (v[k].y ^ (tag >> 1));
            if ((bad & 1u) == 0) break;
            POLL_GUARD(it);
        }
        float s0 = 0.f, s1 = 0.f, s2 = 0.f, s3 = 0.f;
#pragma unroll
        for (int k = 0; k < 5; k++) { s0 += bf_lo(v[k].x); s1 += bf_hi(v[k].x); s2 += bf_lo(v[k].y); s3 += bf_hi(v[k].y); }
        sts128(sb + SF_RED + tid * 16, __float_as_uint(s0), __float_as_uint(s1), __float_as_uint(s2), __float_as_uint(s3));
        __syncwarp();
        bar_arrive(11, 448);
    }
}

__global__ void __cluster_dims__(2, 1, 1) __launch_bounds__(NTHR, 1)
fused_kernel(const Params p, const __grid_constant__ CUtensorMap mU, const __grid_constant__ CUtensorMap mR, const __grid_constant__ CUtensorMap mG64,
             const __grid_constant__ CUtensorMap mU64, const __grid_constant__ CUtensorMap mG16, const __grid_constant__ CUtensorMap mU16,
             const __grid_constant__ CUtensorMap mWd) {
    extern __shared__ __align__(1024) uint8_t smem_raw[];
    const uint32_t sb = smem_u32(smem_raw);
    const uint32_t t0 = clk();
    const int bx = blockIdx.x;
    const int lane = threadIdx.x & 31, f = bx - FFN0, cb = bx < FFN0 ? bx : bx - NFFN;
    const bool ffn = (unsigned)f < NFFN;
    const int nch = (unsigned)f < 48 ? 5 : 4, c0 = ffn ? (nch == 5 ? 5 * f : 4 * f + 48) : 4 * cb;
    const int warp = warp_id();
    KParams kp;
    {
        const int w = threadIdx.x >> 5, h = w >= nch, c = c0 + w - nch * h;
        if (GDELAY && ffn) spin_until(t0, GDELAY);
        if (w < 2 * nch) kp = kload(p, 2 * (c & ~3) + (ffn ? 4 : 0) + (c & 3), h);
    }
    if (CLR == 2 && ffn && warp < 12) {
        uint2* const pdst = p.scr->part + (3 * warp * NFFN + f) * 32 + lane;
        st_pkt8(pdst, 0, 0); st_pkt8(pdst + NFFN * 32, 0, 0); st_pkt8(pdst + 2 * NFFN * 32, 0, 0);
    }
    const int half = warp >= nch, j = warp - nch * half, ci = c0 + j;
    uint32_t kw[21], q[8][4];
    uint4 k8;
    if (warp < 2 * nch) {
        const uint32_t stage = sb + (ffn ? SF_STG : SC_STG), mine = stage + warp * KG_STAGE, other = stage + (half ? j : warp + nch) * KG_STAGE;
        cluster_arrive_relaxed();
        if (f == 0 && threadIdx.x < 8) st_rlx32(&p.scr->sel[lane], 0);
        float kv[21], fin;
        kgen(kp, mine, kv, fin, sb);
        cluster_wait();
        if (!(ffn || half)) {
            ksend(kv, fin, mine, false);
            bar_arrive(2 + j, 64);
            mbar_wait(sb + SB_UT);
            conv_windows(sb, warp, q);
            bar_sync(11 + j, 64);
            krecv(kv, fin, other, 0, 17);
            k8 = kwords8(kv);
        } else {
            ksend(kv, fin, mine, half);
            if (!ffn) bar_arrive(11 + j, 64);
            bar_sync(2 + j, 64);
            if (half) {
                krecv(kv, fin, other, 0, 0); krecv(kv, fin, other, 1, 4); krecv(kv, fin, other, 2, 8); krecv(kv, fin, other, 3, 12);
                kv[16] = kv[16] * fin + __uint_as_float(lds32(other + 2048)) + bf_lo(kp.dskip);
            } else krecv(kv, fin, other, 0, 17);
            if (ffn) { asm volatile("" :: "f"(kv[0]), "f"(kv[4]), "f"(kv[8]), "f"(kv[12]), "f"(kv[16]), "f"(kv[17]) : "memory"); __syncwarp(); if (lane == 0) mbar_arrive(sb + SF_BAR + 184); }
            if (half) kwords(kv, kw);
            else k8 = kwords8(kv);
            if (!ffn) {
                mbar_wait(sb + SB_UT);
                kstore(kw, sb + SC_KT + j * KT_BYTES);
                bar_arrive(6 + j, 64);
                conv_windows(sb, warp, q);
                k8 = conv_fetch(p, sb, cb, warp, t0);
            }
        }
    }
    if (!(ffn || warp >= 8)) conv_warp(sb, warp, q, k8);
    else if (ffn) ffn_cta(p, &mR, &mG64, &mU64, &mG16, &mU16, &mWd, sb, f, warp, t0, kw, k8, ci);
    else conv_helper(p, &mU, sb, cb, warp - 8, t0);
}

typedef CUresult (*EncodeFn)(CUtensorMap*, CUtensorMapDataType, cuuint32_t, void*, const cuuint64_t*, const cuuint64_t*, const cuuint32_t*, const cuuint32_t*,
                             CUtensorMapInterleave, CUtensorMapSwizzle, CUtensorMapL2promotion, CUtensorMapFloatOOBfill);

CUtensorMap make_map(EncodeFn fn, const void* base, uint64_t inner, uint64_t outer, uint32_t bi, uint32_t bo, CUtensorMapSwizzle sw,
                     CUtensorMapL2promotion pr = CU_TENSOR_MAP_L2_PROMOTION_NONE) {
    CUtensorMap m;
    cuuint64_t dims[2] = {inner, outer};
    cuuint64_t strides[1] = {inner * 2};
    cuuint32_t box[2] = {bi, bo};
    cuuint32_t es[2] = {1, 1};
    fn(&m, CU_TENSOR_MAP_DATA_TYPE_BFLOAT16, 2, (void*)base, dims, strides, box, es, CU_TENSOR_MAP_INTERLEAVE_NONE, sw, pr, CU_TENSOR_MAP_FLOAT_OOB_FILL_NONE);
    return m;
}

}

extern "C" void kernel_launch(void* const* d_in, const int* in_sizes, int n_in, void* d_out, int out_size) {
    (void)in_sizes; (void)n_in; (void)out_size;
    static EncodeFn fn = nullptr;
    static Scratch* scr = nullptr;
    if (!fn) {
        void* ptr = nullptr; cudaDriverEntryPointQueryResult qr;
        cudaGetDriverEntryPoint("cuTensorMapEncodeTiled", &ptr, cudaEnableDefault, &qr);
        fn = (EncodeFn)ptr;
        cudaGetSymbolAddress((void**)&scr, g_scr);
        cudaFuncSetAttribute(fused_kernel, cudaFuncAttributeMaxDynamicSharedMemorySize, SMEM_BYTES);
    }
    typedef const __nv_bfloat16* bp;
    Params p;
    p.u = (bp)d_in[0]; p.Are = (bp)d_in[1]; p.Aim = (bp)d_in[2]; p.Bre = (bp)d_in[3]; p.Bim = (bp)d_in[4]; p.Cre = (bp)d_in[5]; p.Cim = (bp)d_in[6];
    p.logdt = (bp)d_in[7]; p.Dskip = (bp)d_in[8]; p.wr = (bp)d_in[10]; p.gatew = (bp)d_in[14];
    p.out = (__nv_bfloat16*)d_out; p.scr = scr;
    CUtensorMap mU;
    {
        cuuint64_t dims[5] = {DM, 8, 2, L_SEQ / 128, 8};
        cuuint64_t strides[4] = {16 * DM * 2, DM * 2, 128 * DM * 2, 2 * DM * 2};
        cuuint32_t box[5] = {16, 4, 2, 4, 8};
        cuuint32_t es[5] = {1, 1, 1, 1, 1};
        fn(&mU, CU_TENSOR_MAP_DATA_TYPE_BFLOAT16, 5, d_in[0], dims, strides, box, es, CU_TENSOR_MAP_INTERLEAVE_NONE, CU_TENSOR_MAP_SWIZZLE_32B,
           CU_TENSOR_MAP_L2_PROMOTION_NONE, CU_TENSOR_MAP_FLOAT_OOB_FILL_NONE);
    }
    const CUtensorMap mR = make_map(fn, d_in[0], 64, L_SEQ * 9, 64, 72, CU_TENSOR_MAP_SWIZZLE_128B);
    const CUtensorMap mG64 = make_map(fn, d_in[11], FF, DM, 64, 64, CU_TENSOR_MAP_SWIZZLE_128B);
    const CUtensorMap mU64 = make_map(fn, d_in[12], FF, DM, 64, 64, CU_TENSOR_MAP_SWIZZLE_128B);
    const CUtensorMap mG16 = make_map(fn, d_in[11], FF, DM, 16, 64, CU_TENSOR_MAP_SWIZZLE_32B, CU_TENSOR_MAP_L2_PROMOTION_L2_128B);
    const CUtensorMap mU16 = make_map(fn, d_in[12], FF, DM, 16, 64, CU_TENSOR_MAP_SWIZZLE_32B, CU_TENSOR_MAP_L2_PROMOTION_L2_128B);
    const CUtensorMap mWd = make_map(fn, d_in[13], 64, FF * 9, 64, 144, CU_TENSOR_MAP_SWIZZLE_128B);
    fused_kernel<<<NCTA, NTHR, SMEM_BYTES>>>(p, mU, mR, mG64, mU64, mG16, mU16, mWd);
}
```

```cpp
#include <cuda_runtime.h>
#include <cuda_bf16.h>
#include <cuda_fp16.h>
#include <cuda.h>
#include <stdint.h>

#define RDELAY 1000
#define VDELAY 1100
#define HDELAY 2700
#define WDELAY 1800
#define WPER0 890
#define WPER 740
#define DPER 300
#define PDELAY 5300
#define SDELAY 7300
#define KDELAY0 6300
#define KDELAY1 7000
#define KDELAY2 6000
#define GDELAY 400
#define PACE 20
#define SPLITM 3
#define SPLITJ 2
#define AMODE_U 0
#define AMODE_H 3
#define JBAR 1

namespace {

constexpr int L_SEQ = 2048, DM = 576, NST = 128, FF = 4608;
constexpr int NCTA = 132, NFFN = 60, FFN0 = 8, NTHR = 512;
#define NLOW 5
constexpr int NL = NLOW;

struct Scratch {
    unsigned launch; unsigned pad0[31];
    uint32_t sel[32];
    uint32_t zero[72 * 8];
    uint32_t rec[2 * L_SEQ];
    uint4 kx[DM * 4 * 32];
    uint4 part[24 * 30 * 32];
};
__device__ Scratch g_scr;

struct Params {
    const __nv_bfloat16 *Are, *Aim, *Bre, *Bim, *Cre, *Cim, *logdt, *Dskip, *u, *wr, *gatew, *wd;
    __nv_bfloat16* out;
    Scratch* scr;
};

__device__ __forceinline__ uint32_t smem_u32(const void* p) { return (uint32_t)__cvta_generic_to_shared(p); }
__device__ __forceinline__ uint32_t pack_bf16(float lo, float hi) { uint32_t r; asm("cvt.rn.bf16x2.f32 %0, %1, %2;" : "=r"(r) : "f"(hi), "f"(lo)); return r; }
__device__ __forceinline__ uint32_t pack_f16(float lo, float hi) { uint32_t r; asm("cvt.rn.f16x2.f32 %0, %1, %2;" : "=r"(r) : "f"(hi), "f"(lo)); return r; }
__device__ __forceinline__ float bf_lo(uint32_t w) { return __uint_as_float(w << 16); }
__device__ __forceinline__ float bf_hi(uint32_t w) { return __uint_as_float(w & 0xffff0000u); }
__device__ __forceinline__ uint32_t cvt_bf16(float x) { uint32_t r; asm volatile("cvt.rn.bf16x2.f32 %0, %1, %1;" : "=r"(r) : "f"(x)); return r; }
__device__ __forceinline__ float rbf(float x) { return bf_lo(pack_bf16(x, 0.f)); }
__device__ __forceinline__ uint32_t hmul2(uint32_t a, uint32_t b) { __nv_bfloat162 r = __hmul2_rn(*(__nv_bfloat162*)&a, *(__nv_bfloat162*)&b); return *(uint32_t*)&r; }
__device__ __forceinline__ uint32_t hadd2(uint32_t a, uint32_t b) { __nv_bfloat162 r = __hadd2_rn(*(__nv_bfloat162*)&a, *(__nv_bfloat162*)&b); return *(uint32_t*)&r; }
__device__ __forceinline__ uint32_t hfma2(uint32_t a, uint32_t b, uint32_t c) { uint32_t r; asm("fma.rn.bf16x2 %0, %1, %2, %3;" : "=r"(r) : "r"(a), "r"(b), "r"(c)); return r; }
__device__ __forceinline__ uint32_t hsub2(uint32_t a, uint32_t b) { __nv_bfloat162 r = __hsub2_rn(*(__nv_bfloat162*)&a, *(__nv_bfloat162*)&b); return *(uint32_t*)&r; }
__device__ __forceinline__ void mma_bf(float (&c)[4], uint32_t a0, uint32_t a1, uint32_t a2, uint32_t a3, uint32_t b0, uint32_t b1) {
    asm("mma.sync.aligned.m16n8k16.row.col.f32.bf16.bf16.f32 {%0,%1,%2,%3}, {%4,%5,%6,%7}, {%8,%9}, {%0,%1,%2,%3};"
        : "+f"(c[0]), "+f"(c[1]), "+f"(c[2]), "+f"(c[3]) : "r"(a0), "r"(a1), "r"(a2), "r"(a3), "r"(b0), "r"(b1));
}
__device__ __forceinline__ void mma_bf0(float (&c)[4], uint32_t a0, uint32_t a1, uint32_t a2, uint32_t a3, uint32_t b0, uint32_t b1) {
    asm("mma.sync.aligned.m16n8k16.row.col.f32.bf16.bf16.f32 {%0,%1,%2,%3}, {%4,%5,%6,%7}, {%8,%9}, {%10,%10,%10,%10};"
        : "=f"(c[0]), "=f"(c[1]), "=f"(c[2]), "=f"(c[3]) : "r"(a0), "r"(a1), "r"(a2), "r"(a3), "r"(b0), "r"(b1), "f"(0.f));
}
__device__ __forceinline__ void mma_bf8(float (&c)[4], uint32_t a0, uint32_t a1, uint32_t b0) {
    asm("mma.sync.aligned.m16n8k8.row.col.f32.bf16.bf16.f32 {%0,%1,%2,%3}, {%4,%5}, {%6}, {%0,%1,%2,%3};"
        : "+f"(c[0]), "+f"(c[1]), "+f"(c[2]), "+f"(c[3]) : "r"(a0), "r"(a1), "r"(b0));
}
__device__ __forceinline__ void mma_f16(float (&c)[4], uint32_t a0, uint32_t a1, uint32_t a2, uint32_t a3, uint32_t b0, uint32_t b1) {
    asm("mma.sync.aligned.m16n8k16.row.col.f32.f16.f16.f32 {%0,%1,%2,%3}, {%4,%5,%6,%7}, {%8,%9}, {%0,%1,%2,%3};"
        : "+f"(c[0]), "+f"(c[1]), "+f"(c[2]), "+f"(c[3]) : "r"(a0), "r"(a1), "r"(a2), "r"(a3), "r"(b0), "r"(b1));
}
__device__ __forceinline__ uint32_t lds16(uint32_t a) { uint32_t v; asm volatile("ld.shared.u16 %0, [%1];" : "=r"(v) : "r"(a)); return v; }
__device__ __forceinline__ uint32_t lds8(uint32_t a) { uint32_t v; asm volatile("ld.shared.u8 %0, [%1];" : "=r"(v) : "r"(a)); return v; }
__device__ __forceinline__ uint32_t lds32(uint32_t a) { uint32_t v; asm volatile("ld.shared.u32 %0, [%1];" : "=r"(v) : "r"(a)); return v; }
__device__ __forceinline__ uint32_t lds32v(uint32_t a) { uint32_t v; asm volatile("ld.volatile.shared.u32 %0, [%1];" : "=r"(v) : "r"(a)); return v; }
__device__ __forceinline__ uint2 lds64(uint32_t a) { uint2 v; asm volatile("ld.shared.v2.u32 {%0,%1}, [%2];" : "=r"(v.x), "=r"(v.y) : "r"(a)); return v; }
__device__ __forceinline__ uint4 lds128(uint32_t a) { uint4 v; asm volatile("ld.shared.v4.u32 {%0,%1,%2,%3}, [%4];" : "=r"(v.x), "=r"(v.y), "=r"(v.z), "=r"(v.w) : "r"(a)); return v; }
__device__ __forceinline__ void ldsm4(uint32_t (&r)[4], uint32_t a) {
    asm volatile("ldmatrix.sync.aligned.m8n8.x4.shared.b16 {%0,%1,%2,%3}, [%4];" : "=r"(r[0]), "=r"(r[1]), "=r"(r[2]), "=r"(r[3]) : "r"(a));
}
__device__ __forceinline__ void ldsm2(uint32_t (&r)[4], uint32_t a) {
    asm volatile("ldmatrix.sync.aligned.m8n8.x2.shared.b16 {%0,%1}, [%2];" : "=r"(r[0]), "=r"(r[1]) : "r"(a));
}
__device__ __forceinline__ void ldsm4t(uint32_t (&r)[4], uint32_t a) {
    asm volatile("ldmatrix.sync.aligned.m8n8.x4.trans.shared.b16 {%0,%1,%2,%3}, [%4];" : "=r"(r[0]), "=r"(r[1]), "=r"(r[2]), "=r"(r[3]) : "r"(a));
}
__device__ __forceinline__ void sts16(uint32_t a, uint32_t v) { asm volatile("st.shared.u16 [%0], %1;" :: "r"(a), "r"(v) : "memory"); }
__device__ __forceinline__ void sts32(uint32_t a, uint32_t v) { asm volatile("st.shared.u32 [%0], %1;" :: "r"(a), "r"(v) : "memory"); }
__device__ __forceinline__ void sts64(uint32_t a, uint32_t x, uint32_t y) { asm volatile("st.shared.v2.u32 [%0], {%1,%2};" :: "r"(a), "r"(x), "r"(y) : "memory"); }
__device__ __forceinline__ void sts128(uint32_t a, uint32_t x, uint32_t y, uint32_t z, uint32_t w) {
    asm volatile("st.shared.v4.u32 [%0], {%1,%2,%3,%4};" :: "r"(a), "r"(x), "r"(y), "r"(z), "r"(w) : "memory");
}
__device__ __forceinline__ void stsm2(uint32_t a, uint32_t x, uint32_t y) {
    asm volatile("stmatrix.sync.aligned.m8n8.x2.shared.b16 [%0], {%1,%2};" :: "r"(a), "r"(x), "r"(y) : "memory");
}
__device__ __forceinline__ void stsm4t(uint32_t a, uint32_t r0, uint32_t r1, uint32_t r2, uint32_t r3) {
    asm volatile("stmatrix.sync.aligned.m8n8.x4.trans.shared.b16 [%0], {%1,%2,%3,%4};" :: "r"(a), "r"(r0), "r"(r1), "r"(r2), "r"(r3) : "memory");
}
__device__ __forceinline__ void st_async32(uint32_t a, uint32_t x, uint32_t bar) {
    asm volatile("st.async.weak.shared::cluster.mbarrier::complete_tx::bytes.b32 [%0], %1, [%2];" :: "r"(a), "r"(x), "r"(bar) : "memory");
}
__device__ __forceinline__ void st_async128(uint32_t a, uint32_t x, uint32_t y, uint32_t z, uint32_t w, uint32_t bar) {
    asm volatile("st.async.weak.shared::cluster.mbarrier::complete_tx::bytes.v4.b32 [%0], {%1,%2,%3,%4}, [%5];" :: "r"(a), "r"(x), "r"(y), "r"(z), "r"(w), "r"(bar) : "memory");
}
__device__ __forceinline__ void mbar_init(uint32_t b, uint32_t cnt) { asm volatile("mbarrier.init.shared::cta.b64 [%0], %1;" :: "r"(b), "r"(cnt) : "memory"); }
__device__ __forceinline__ void mbar_fence_init() { asm volatile("fence.mbarrier_init.release.cluster;" ::: "memory"); }
__device__ __forceinline__ void mbar_expect(uint32_t b, uint32_t bytes) { asm volatile("mbarrier.arrive.expect_tx.shared::cta.b64 _, [%0], %1;" :: "r"(b), "r"(bytes) : "memory"); }
__device__ __forceinline__ void mbar_arrive(uint32_t b) { asm volatile("mbarrier.arrive.shared::cta.b64 _, [%0];" :: "r"(b) : "memory"); }
__device__ __forceinline__ void mbar_arrive_peer(uint32_t b) { asm volatile("mbarrier.arrive.relaxed.cluster.shared::cluster.b64 _, [%0];" :: "r"(b) : "memory"); }
__device__ __forceinline__ void mbar_wait(uint32_t b) {
    asm volatile("{ .reg .pred p;\nW: mbarrier.try_wait.parity.shared::cta.b64 p, [%0], 0; @!p bra W; }" :: "r"(b) : "memory");
}
__device__ __forceinline__ bool mbar_test(uint32_t b) {
    uint32_t d; asm volatile("{ .reg .pred p; mbarrier.test_wait.parity.shared::cta.b64 p, [%1], 0; selp.u32 %0, 1, 0, p; }" : "=r"(d) : "r"(b) : "memory"); return d;
}
__device__ __forceinline__ void tma2d(uint32_t dst, const CUtensorMap* m, int c0, int c1, uint32_t bar) {
    asm volatile("cp.async.bulk.tensor.2d.shared::cluster.global.mbarrier::complete_tx::bytes [%0], [%1, {%3, %4}], [%2];"
                 :: "r"(dst), "l"(m), "r"(bar), "r"(c0), "r"(c1) : "memory");
}
__device__ __forceinline__ void tma3d(uint32_t dst, const CUtensorMap* m, int c0, int c1, int c2, uint32_t bar) {
    asm volatile("cp.async.bulk.tensor.3d.shared::cluster.global.mbarrier::complete_tx::bytes [%0], [%1, {%3, %4, %5}], [%2];"
                 :: "r"(dst), "l"(m), "r"(bar), "r"(c0), "r"(c1), "r"(c2) : "memory");
}
__device__ __forceinline__ void tma5d(uint32_t dst, const CUtensorMap* m, int c0, int c1, int c2, int c3, int c4, uint32_t bar) {
    asm volatile("cp.async.bulk.tensor.5d.shared::cluster.global.mbarrier::complete_tx::bytes [%0], [%1, {%3, %4, %5, %6, %7}], [%2];"
                 :: "r"(dst), "l"(m), "r"(bar), "r"(c0), "r"(c1), "r"(c2), "r"(c3), "r"(c4) : "memory");
}
__device__ __forceinline__ void bulk_load(uint32_t dst, const void* src, uint32_t bytes, uint32_t bar) {
    asm volatile("cp.async.bulk.shared::cluster.global.mbarrier::complete_tx::bytes [%0], [%1], %2, [%3];" :: "r"(dst), "l"(src), "r"(bytes), "r"(bar) : "memory");
}
__device__ __forceinline__ bool elect() { uint32_t d; asm volatile("{ .reg .pred p; elect.sync _|p, 0xffffffff; selp.u32 %0, 1, 0, p; }" : "=r"(d)); return d; }
__device__ __forceinline__ void prefetch_l2(const void* src, uint32_t bytes) { asm volatile("cp.async.bulk.prefetch.L2.global [%0], %1;" :: "l"(src), "r"(bytes) : "memory"); }
__device__ __forceinline__ uint32_t mapa(uint32_t a, uint32_t rank) { uint32_t r; asm("mapa.shared::cluster.u32 %0, %1, %2;" : "=r"(r) : "r"(a), "r"(rank)); return r; }
__device__ __forceinline__ void prefetch_map(const CUtensorMap* m) { asm volatile("prefetch.tensormap [%0];" :: "l"(m) : "memory"); }
__device__ __forceinline__ void bar_sync(int id, int n) { asm volatile("bar.sync %0, %1;" :: "r"(id), "r"(n) : "memory"); }
__device__ __forceinline__ void bar_arrive(int id, int n) { asm volatile("bar.arrive %0, %1;" :: "r"(id), "r"(n) : "memory"); }
__device__ __forceinline__ void cluster_arrive_relaxed() { asm volatile("barrier.cluster.arrive.relaxed.aligned;" ::: "memory"); }
__device__ __forceinline__ void cluster_wait() { asm volatile("barrier.cluster.wait.aligned;" ::: "memory"); }
__device__ __forceinline__ uint32_t ld_rlx32(const void* p) { uint32_t v; asm volatile("ld.relaxed.gpu.global.u32 %0, [%1];" : "=r"(v) : "l"(p) : "memory"); return v; }
__device__ __forceinline__ uint4 ld_rlx128(const void* p) {
    uint4 v; asm volatile("ld.relaxed.gpu.global.v4.u32 {%0,%1,%2,%3}, [%4];" : "=r"(v.x), "=r"(v.y), "=r"(v.z), "=r"(v.w) : "l"(p) : "memory"); return v;
}
__device__ __forceinline__ uint32_t ld_acq32(const void* p) { uint32_t v; asm volatile("ld.acquire.gpu.global.u32 %0, [%1];" : "=r"(v) : "l"(p) : "memory"); return v; }
__device__ __forceinline__ void red_bf2(void* p, uint32_t v) { asm volatile("red.relaxed.gpu.global.add.noftz.bf16x2 [%0], %1;" :: "l"(p), "r"(v) : "memory"); }
__device__ __forceinline__ uint32_t take_ticket(unsigned* p) { uint32_t v; asm volatile("atom.relaxed.gpu.global.add.u32 %0, [%1], 1;" : "=r"(v) : "l"(p) : "memory"); return v; }
__device__ __forceinline__ void st_rlx32(void* p, uint32_t v) { asm volatile("st.relaxed.gpu.global.u32 [%0], %1;" :: "l"(p), "r"(v) : "memory"); }
__device__ __forceinline__ void st_pkt(void* p, uint32_t x, uint32_t y, uint32_t z, uint32_t w) {
    asm volatile("{ .reg .b64 lo, hi; .reg .b128 v; mov.b64 lo, {%1, %2}; mov.b64 hi, {%3, %4}; mov.b128 v, {lo, hi}; st.relaxed.gpu.global.b128 [%0], v; }"
                 :: "l"(p), "r"(x), "r"(y), "r"(z), "r"(w) : "memory");
}
__device__ __forceinline__ uint4 ld_pkt(const void* p) {
    uint4 r;
    asm volatile("{ .reg .b64 lo, hi; .reg .b128 v; ld.relaxed.gpu.global.b128 v, [%4]; mov.b128 {lo, hi}, v; mov.b64 {%0, %1}, lo; mov.b64 {%2, %3}, hi; }"
                 : "=r"(r.x), "=r"(r.y), "=r"(r.z), "=r"(r.w) : "l"(p) : "memory");
    return r;
}
__device__ __forceinline__ void st_pkt8(void* p, uint32_t x, uint32_t y) {
    asm volatile("{ .reg .b64 v; mov.b64 v, {%1, %2}; st.relaxed.gpu.global.b64 [%0], v; }" :: "l"(p), "r"(x), "r"(y) : "memory");
}
__device__ __forceinline__ uint2 ld_pkt8(const void* p) {
    uint2 r; asm volatile("{ .reg .b64 v; ld.relaxed.gpu.global.b64 v, [%2]; mov.b64 {%0, %1}, v; }" : "=r"(r.x), "=r"(r.y) : "l"(p) : "memory"); return r;
}
__device__ __forceinline__ uint32_t tag_of(uint32_t ticket) { return ticket / NCTA % 3u + 1u; }
__device__ __forceinline__ uint2 ldg64(const void* p) { uint2 v; asm volatile("ld.global.nc.v2.u32 {%0,%1}, [%2];" : "=r"(v.x), "=r"(v.y) : "l"(p)); return v; }
__device__ __forceinline__ uint4 ldg128(const void* p) { uint4 v; asm volatile("ld.global.nc.v4.u32 {%0,%1,%2,%3}, [%4];" : "=r"(v.x), "=r"(v.y), "=r"(v.z), "=r"(v.w) : "l"(p)); return v; }
__device__ __forceinline__ uint32_t ldg32(const void* p) { uint32_t v; asm volatile("ld.global.nc.u32 %0, [%1];" : "=r"(v) : "l"(p)); return v; }
__device__ __forceinline__ uint32_t ldg16(const void* p) { uint32_t v; asm volatile("ld.global.nc.u16 %0, [%1];" : "=r"(v) : "l"(p)); return v; }
__device__ __forceinline__ int warp_id() { return __shfl_sync(0xffffffffu, threadIdx.x >> 5, 0); }
__device__ __forceinline__ uint32_t clk() { uint32_t t; asm volatile("mov.u32 %0, %clock;" : "=r"(t) :: "memory"); return t; }
__device__ __forceinline__ void spin_until(uint32_t t0, uint32_t d) { while (clk() - t0 < d) {} }
__device__ __forceinline__ float sigmoidf_(float x) { return __fdividef(1.0f, 1.0f + __expf(-x)); }
__device__ __forceinline__ int key_row(uint32_t key) { return 2047 - (int)(key & 2047u); }
__device__ __forceinline__ uint32_t key_thr(uint32_t key) { return __byte_perm(key & 2047u, key << 3, 0x7610); }
__device__ __forceinline__ float key_val(uint32_t key) {
    const uint32_t o = (key << 3) & 0xffff0000u; return __uint_as_float((o & 0x80000000u) ? (o & 0x7fffffffu) : (~o & 0xffff0000u));
}
#define RARE(x) __builtin_expect(!!(x), 0)
#define POLL_GUARD(it) (void)(it)

constexpr int UT_PL = 2240, UT_STRIDE = 4544;
constexpr int KT_P = 0, KT_P4 = 544 * 4, KT_P8 = KT_P4 + 172 * 4, KT_BYTES = KT_P8 + 140 * 4;
constexpr int KG_ROW = 272, KG_STAGE = 33 * KG_ROW;
constexpr int OUT_HALF = 2368, OUT_STAGE = 2 * OUT_HALF;
constexpr int SC_UTILE = 0;
constexpr int SC_UT = 32768;
constexpr int SC_STG = SC_UT + 8 * UT_STRIDE;
constexpr int SC_KT = SC_STG + 8 * KG_STAGE;
constexpr int SC_OUT = SC_KT + 8 * KT_BYTES;
constexpr int SC_CT = SC_OUT + 8 * OUT_STAGE;
constexpr int SC_BAR = SC_CT + 2560;
constexpr int SB_UT = SC_BAR + 32, SB_OUT = SC_BAR + 64, SC_KEY = SC_BAR + 128, SC_TAG = SC_BAR + 160;
constexpr int SC_END = SC_BAR + 256;
static_assert(SC_STG % 128 == 0 && SC_OUT % 128 == 0 && SC_KT % 16 == 0, "align");
constexpr int PIECE_P = 24576, PIECE_H = 16384, DPIECE = 18432;
constexpr int SF_LIST = 9 * PIECE_P, SF_WR = SF_LIST + 4096;
constexpr int SF_XS = SF_LIST + 384;
constexpr int SF_BAR = SF_XS + 9344;
constexpr int FB_W = SF_BAR, FB_D = FB_W + 72, FB_FREE = FB_D + 48, FB_SEL = FB_FREE + 48, FB_KG = FB_SEL + 8, FB_TK = FB_KG + 8, FB_UT = FB_TK + 8, FB_GU = FB_UT + 8,
              FB_X = FB_GU + 8, FB_WR = FB_X + 8, FB_PEER = FB_WR + 8, FB_R = FB_PEER + 8, FB_RAW = FB_R + 48;
constexpr int SF_MAX = FB_RAW + 8, SF_CNT = SF_MAX + 64, SF_TK = SF_CNT + 4, SF_CLK = SF_CNT + 8, SF_TN = SF_CNT + 16, SF_SEL = SF_CNT + 32;
constexpr int SF_END = SF_SEL + 32;
constexpr int SP_R = 83 * 1024, SP_STG = SF_LIST - 12 * KG_STAGE, SP_H = DPIECE, SP_EX = PIECE_P + DPIECE, SP_RED = 6 * PIECE_P;
constexpr int UH_PL = 128 + 128 * NL + 64, UH_STRIDE = 2 * UH_PL - 64, UH_HI = 8 * UH_STRIDE + 32, KH_BYTES = KT_P4 + 176 * 4, OH_STRIDE = 512 * ((NL + 1) / 2) + 64;
constexpr int SH_UT = 9 * PIECE_H, SH_R = SH_UT, SH_R5 = 4 * PIECE_H, SH_STG = SH_UT - 8 * KG_STAGE, SH_H = SH_UT + 16 * UH_STRIDE + 128, SH_OUT = SH_H + 2560;
constexpr int SH_CT = SH_R + 5 * 9216, SH_RAW = SF_LIST - NL * 4096, SH_KT = SF_LIST - 8 * KH_BYTES;
constexpr int SM_TIM = SF_END;
constexpr int SMEM_BYTES = SF_END + 272;
static_assert(SP_R + 3 * 9216 <= SP_STG && SP_R >= 3 * PIECE_P && SP_STG >= 4 * PIECE_P && SH_R5 + 9216 <= SH_STG && SH_OUT + 8 * OH_STRIDE <= SH_CT && (SH_KT - SH_OUT) % 64 == 0 && KH_BYTES % 128 == 64 && SH_CT + 2560 <= SH_RAW &&
              SH_CT + 2560 <= SH_KT && SF_MAX % 16 == 0 && SMEM_BYTES <= 232448 && SC_END <= SF_END, "smem");

struct cplx { float re, im; };
struct h2c { uint32_t re, im; };
__device__ __forceinline__ cplx csq(cplx a) {
    cplx r; r.re = a.re * a.re - a.im * a.im;
    asm("{ .reg .f32 t; mul.f32 t, %1, %2; mul.f32 %0, t, 0f40000000; }" : "=f"(r.im) : "f"(a.re), "f"(a.im));
    return r;
}
__device__ __forceinline__ float ex2(float x) { float m; asm("ex2.approx.ftz.f32 %0, %1;" : "=f"(m) : "f"(x)); return m; }
__device__ __forceinline__ cplx cexp2(float x, float y) {
    const float m = ex2(x);
    cplx o; o.re = m * __cosf(y); o.im = m * __sinf(y); return o;
}
__device__ __forceinline__ h2c hpack(cplx a, cplx b) { h2c r; r.re = pack_f16(a.re, b.re); r.im = pack_f16(a.im, b.im); return r; }
__device__ __forceinline__ h2c hmulc(h2c a, h2c m) {
    h2c r;
    asm("{ .reg .b32 s, t; mul.f16x2 s, %3, %5; mul.f16x2 t, %3, %4; neg.f16x2 s, s; fma.rn.f16x2 %0, %2, %4, s; fma.rn.f16x2 %1, %2, %5, t; }"
        : "=&r"(r.re), "=r"(r.im) : "r"(a.re), "r"(a.im), "r"(m.re), "r"(m.im));
    return r;
}
__device__ __forceinline__ h2c hmulj(h2c a, h2c m) {
    h2c r;
    asm("{ .reg .b32 s, t; mul.f16x2 s, %3, %5; mul.f16x2 t, %2, %5; neg.f16x2 t, t; fma.rn.f16x2 %0, %2, %4, s; fma.rn.f16x2 %1, %3, %4, t; }"
        : "=&r"(r.re), "=r"(r.im) : "r"(a.re), "r"(a.im), "r"(m.re), "r"(m.im));
    return r;
}

struct KParams { uint32_t v[6], logdt, dskip; };
__device__ __forceinline__ KParams kload(const Params& p, int ch, int half) {
    KParams k;
    const int o = ch * NST + 64 * half + 2 * (threadIdx.x & 31);
    const __nv_bfloat16* a[8] = {p.Are + o, p.Aim + o, p.Bre + o, p.Bim + o, p.Cre + o, p.Cim + o, p.logdt + ch, p.Dskip + ch};
#pragma unroll
    for (int i = 0; i < 6; i++) k.v[i] = ldg32(a[i]);
    k.logdt = ldg16(a[6]);
    k.dskip = ldg16(a[7]);
    return k;
}

__device__ __forceinline__ void kgen(const KParams& k, uint32_t stage, float (&kv)[21], float& fin, uint32_t sb) {
    const int lane = threadIdx.x & 31, mi = lane >> 3, r8 = lane & 7;
    const uint32_t (&v)[6] = k.v;
    const uint32_t w2 = stage + (lane & 15) * 16, w1 = stage + lane * 4;
    auto put = [&](int row, h2c x) { stsm2(w2 + row * KG_ROW, x.re, x.im); };
    auto keep = [&](int row, h2c x) { sts32(w1 + row * KG_ROW, x.re); sts32(w1 + row * KG_ROW + 128, x.im); };
    sts32(w1, 0x3c003c00u); sts32(w1 + 128, 0u);
    const float dt = rbf(ex2(bf_lo(k.logdt) * 1.4426950408889634f));
    const float dl = dt * 1.4426950408889634f;
    const float xa = bf_lo(v[0]) * dl, xb = bf_hi(v[0]) * dl, ya = bf_lo(v[1]) * dt, yb = bf_hi(v[1]) * dt;
    cplx a = cexp2(xa, ya), b = cexp2(xb, yb), c = cexp2(64.f * xa, 64.f * ya), d = cexp2(64.f * xb, 64.f * yb);
    cplx Wa, Wb;
    Wa.re = bf_lo(v[4]) * bf_lo(v[2]) - bf_lo(v[5]) * bf_lo(v[3]); Wa.im = bf_lo(v[4]) * bf_lo(v[3]) + bf_lo(v[5]) * bf_lo(v[2]);
    Wb.re = bf_hi(v[4]) * bf_hi(v[2]) - bf_hi(v[5]) * bf_hi(v[3]); Wb.im = bf_hi(v[4]) * bf_hi(v[3]) + bf_hi(v[5]) * bf_hi(v[2]);
    const float mx = fmaxf(fmaxf(fabsf(Wa.re), fabsf(Wa.im)), fmaxf(fabsf(Wb.re), fabsf(Wb.im)));
    const uint32_t ex = max(__reduce_max_sync(0xffffffffu, __float_as_uint(mx)) >> 23, 10u);
    const float sc = __uint_as_float((263u - ex) << 23);
    fin = dt * __uint_as_float((ex - 9u) << 23);
    Wa.re *= sc; Wa.im *= sc; Wb.re *= sc; Wb.im *= sc;
    kv[16] = (float)__reduce_add_sync(0xffffffffu, __float2int_rn((Wa.re + Wb.re) * 32768.f)) * (1.f / 32768.f);
    h2c c1;
    {
        cplx p, q;
        p.re = Wa.re * a.re - Wa.im * a.im; p.im = -(Wa.re * a.im) - Wa.im * a.re; q.re = Wb.re * b.re - Wb.im * b.im; q.im = -(Wb.re * b.im) - Wb.im * b.re;
        c1 = hpack(p, q);
    }
    const h2c z1 = hpack(a, b); a = csq(a); b = csq(b);
    const h2c z64 = hpack(c, d); c = csq(c); d = csq(d);
    const h2c z2 = hpack(a, b); a = csq(a); b = csq(b);
    const h2c z128 = hpack(c, d); c = csq(c); d = csq(d);
    const h2c z4 = hpack(a, b); a = csq(a); b = csq(b);
    const h2c z256 = hpack(c, d); c = csq(c); d = csq(d);
    const h2c z8 = hpack(a, b); a = csq(a); b = csq(b);
    const h2c z512 = hpack(c, d);
    const h2c z16 = hpack(a, b); a = csq(a); b = csq(b);
    const h2c z32 = hpack(a, b);
    keep(32, z64);
    const h2c c2 = hmulj(c1, z1), c3 = hmulj(c1, z2), c4 = hmulj(c2, z2), c6 = hmulj(c2, z4), c8 = hmulj(c4, z4);
    keep(8, c1); keep(9, c2); keep(10, c3); keep(11, c4); put(12, hmulj(c1, z4)); keep(13, c6); put(14, hmulj(c3, z4)); keep(15, c8);
    const h2c e260 = hmulj(c4, z256), e264 = hmulj(c8, z256), e776 = hmulj(e264, z512), e840 = hmulj(e776, z64);
    put(16, hmulj(c2, z256)); put(17, hmulj(c4, z512)); keep(18, e260); put(19, hmulj(c8, z512)); put(20, hmulj(c6, z256)); put(21, hmulj(e260, z512)); keep(22, e264); keep(23, e776);
    const h2c z24 = hmulc(z8, z16);
    keep(1, z8); keep(2, z16); keep(3, z24); keep(4, z32); put(5, hmulc(z8, z32)); put(6, hmulc(z16, z32)); put(7, hmulc(z24, z32));
    const h2c d0 = hmulj(e840, z128), d1 = hmulj(e840, z256), d3 = hmulj(e840, z512), d2 = hmulj(d0, z256);
    keep(24, d0); keep(25, d1); keep(27, d3); keep(26, d2); put(28, hmulj(d0, z512)); put(29, hmulj(d1, z512)); put(31, hmulj(d3, z512)); put(30, hmulj(d2, z512));
    __syncwarp();
    cluster_wait();
    const uint32_t ra = stage + ((mi & 1) ? 32 : r8) * KG_ROW + (mi >> 1) * 128, rb = stage + (8 + r8) * KG_ROW + (mi & 1) * 128 + (mi >> 1) * 16;
    float acc[5][4];
#pragma unroll
    for (int i = 0; i < 5; i++) acc[i][0] = acc[i][1] = acc[i][2] = acc[i][3] = 0.f;
#pragma unroll
    for (int s = 0; s < 4; s++) {
        uint32_t A[2][4], B[3][4];
        ldsm4(A[0], ra + 32 * s); ldsm4(A[1], ra + 32 * s + 16);
        ldsm4(B[0], rb + 32 * s); ldsm4(B[1], rb + 32 * s + 8 * KG_ROW); ldsm4(B[2], rb + 32 * s + 16 * KG_ROW);
#pragma unroll
        for (int e = 0; e < 2; e++) {
            const h2c p0 = {A[e][0], A[e][2]}, m = {A[e][1], A[e][3]};
            const h2c p1 = hmulc(p0, m), p2 = hmulc(p1, m), p3 = hmulc(p2, m);
            mma_f16(acc[1], p1.re, p2.re, p1.im, p2.im, B[0][2 * e], B[0][2 * e + 1]);
            mma_f16(acc[3], p1.re, p2.re, p1.im, p2.im, B[1][2 * e], B[1][2 * e + 1]);
            mma_f16(acc[4], p1.re, p2.re, p1.im, p2.im, B[2][2 * e], B[2][2 * e + 1]);
            mma_f16(acc[0], p0.re, p3.re, p0.im, p3.im, B[0][2 * e], B[0][2 * e + 1]);
            mma_f16(acc[2], p0.re, p3.re, p0.im, p3.im, B[1][2 * e], B[1][2 * e + 1]);
        }
    }
#pragma unroll
    for (int q = 0; q < 4; q++) {
        const int i = (q == 1 || q == 2), h = 2 * (q >> 1);
        kv[2 * q] = acc[i][h]; kv[2 * q + 1] = acc[i][h + 1]; kv[8 + q] = acc[2 + i][h]; kv[12 + q] = acc[2 + i][h + 1]; kv[17 + q] = acc[4][2 * (q & 1) + (q >> 1)];
    }
}
__device__ __forceinline__ void ksend(const float (&kv)[21], float fin, uint32_t mine, bool second) {
    const uint32_t lo = (threadIdx.x & 31) * 16;
    auto send = [&](int i, int k) { sts128(mine + lo + 512 * i, __float_as_uint(kv[k] * fin), __float_as_uint(kv[k + 1] * fin), __float_as_uint(kv[k + 2] * fin), __float_as_uint(kv[k + 3] * fin)); };
    __syncwarp();
    if (second) send(0, 17);
    else { send(0, 0); send(1, 4); send(2, 8); send(3, 12); sts32(mine + 2048, __float_as_uint(kv[16] * fin)); }
}
__device__ __forceinline__ void krecv(float (&kv)[21], float fin, uint32_t other, int i, int k) {
    const uint4 x = lds128(other + (threadIdx.x & 31) * 16 + 512 * i);
    kv[k] = kv[k] * fin + __uint_as_float(x.x); kv[k + 1] = kv[k + 1] * fin + __uint_as_float(x.y); kv[k + 2] = kv[k + 2] * fin + __uint_as_float(x.z); kv[k + 3] = kv[k + 3] * fin + __uint_as_float(x.w);
}

__device__ __forceinline__ void kpack(const float (&kv)[21], uint4 (&x)[4]) {
    const int lane = threadIdx.x & 31;
    const uint32_t w512 = pack_bf16(__shfl_sync(0xffffffffu, kv[11], 31), 0.f);
    const float up = __shfl_up_sync(0xffffffffu, kv[15], 2), k512 = bf_lo(w512);
    x[0] = make_uint4(pack_bf16(kv[1], kv[3]), pack_bf16(kv[5], kv[7]), pack_bf16(kv[8], kv[9]), w512);
    x[1] = make_uint4(pack_bf16(kv[10], lane < 30 ? kv[11] : lane == 31 ? 0.f : kv[11] - k512), pack_bf16(kv[0], kv[2]), pack_bf16(kv[4], kv[6]), 0);
    x[2] = make_uint4(pack_bf16(kv[12], kv[13]), pack_bf16(kv[14], kv[15]), pack_bf16((lane & 2) ? up : lane == 29 ? k512 : 0.f, kv[16]), 0);
}
__device__ __forceinline__ void kstore(const uint4 (&x)[4], uint32_t kt) {
    const int lane = threadIdx.x & 31, g = lane >> 2, t = lane & 3;
    const uint32_t h[4] = {x[0].x, x[0].y, x[0].z, x[1].x}, l[2] = {x[1].y, x[1].z};
    const uint32_t sp = lane ? 0x3210 : 0x1076, sa = (lane & 1) ? 0x5410 : 0x5454, sb = (lane & 1) ? 0x1010 : 0x5410;
    uint32_t carry = x[2].z;
    if (lane == 0) sts32(kt + KT_P + 15 * 4, carry >> 16);
#pragma unroll
    for (int i = 0; i < 4; i++) {
        const uint32_t sh = __shfl_sync(0xffffffffu, h[i], (lane + 31) & 31), pv = __byte_perm(sh, carry, sp);
        carry = sh;
#pragma unroll
        for (int e = 0; e < 2; e++) {
            const uint32_t a = kt + KT_P + (128 * i + 64 * e + 16) * 4 + lane * 8;
            if (i < 2) sts64(a, __byte_perm(l[i], pv, 0x5410 + 0x2222 * e), __byte_perm(h[i], l[i], 0x5410 + 0x2222 * e));
            else sts64(a, __byte_perm(h[i], pv, sa + 0x2222 * e), __byte_perm(h[i], pv, sb + 0x2222 * e));
        }
    }
    const uint32_t a4 = kt + KT_P4 + (13 + 2 * g + (t & 1) + 64 * (t >> 1)) * 4;
    sts32(a4, __byte_perm(x[2].x, x[2].z, 0x5410)); sts32(a4 + 64, __byte_perm(x[2].x, 0, 0x1032));
    sts32(a4 + 128, __byte_perm(x[2].y, x[2].x, 0x7610)); sts32(a4 + 192, __byte_perm(x[2].y, 0, 0x1032));
    sts32(t >= 2 ? a4 + 256 : kt + KT_P4 + 12 * 4, __byte_perm(x[2].y, x[0].w, t >= 2 ? 0x3277 : 0x7754));
}
__device__ __forceinline__ uint4 kwords8(const float (&kv)[21]) {
    const float up = __shfl_up_sync(0xffffffffu, kv[20], 1);
    return make_uint4(pack_bf16(kv[17], (threadIdx.x & 3) ? up : 0.f), pack_bf16(kv[18], kv[17]), pack_bf16(kv[19], kv[18]), pack_bf16(kv[20], kv[19]));
}

__device__ __forceinline__ uint32_t band(int e, int c, int h) {
    return (((unsigned)(e - c + h) <= 2u * h) ? 0x3f80u : 0u) | (((unsigned)(e + 1 - c + h) <= 2u * h) ? 0x3f800000u : 0u);
}

template <int UT_PL>
__device__ __forceinline__ void conv_consts(uint32_t a, uint32_t out, uint32_t bar) {
    const int lane = threadIdx.x & 31, g = lane >> 2, t = lane & 3, mi = lane >> 3, r8 = lane & 7, d0 = g - 2 * t, pg = (g >> 1) + 4 * (g & 1);
    a += lane * 16;
    sts128(a, band(4 * t, 4 + g, 4), band(4 * t, 4 + g, 3), band(4 * t + 2, 4 + g, 4), band(4 * t + 2, 4 + g, 3));
    sts128(a + 512, pg * 16 + (t == 0 ? UT_PL - 8 : t == 3 ? UT_PL : 8 * (t - 1)), pg * 16 + (t == 0 ? -8 : t == 3 ? 0 : UT_PL - 16 + 8 * (t - 1)),
           (mi & 1) * UT_PL + (mi >> 1) * 128 + r8 * 16, KT_P + (15 + d0) * 4);
    sts128(a + 1024, (((unsigned)(d0 - 3) < 2u) ? 0xffffu : 0u) | (((unsigned)(d0 - 4) < 2u) ? 0xffff0000u : 0u),
           (((unsigned)(d0 + 5) < 2u) ? 0xffffu : 0u) | (((unsigned)(d0 + 4) < 2u) ? 0xffff0000u : 0u), KT_P4 + (3 + g - t) * 16, UT_PL - 16 + lane * 16);
    sts128(a + 1536, band(2 * t, 6 + g, 2), band(2 * t, 2 + g, 1), band(2 * t + 8, 6 + g, 2), band(2 * t + 8, 2 + g, 1));
    sts128(a + 2048, pg * 16 + (t == 3 ? UT_PL : 4 + 4 * t), pg * 16 + (t == 3 ? 16 : UT_PL + 4 + 4 * t),
           mapa(out + g * 32 + (t & 1) * 16, t >> 1), mapa(bar, t >> 1));
}

__device__ __forceinline__ void conv_windows(uint32_t sb, int warp, uint32_t (&q)[8][4]) {
    const uint32_t ut = sb + SC_UT + warp * UT_STRIDE + 128, ct = sb + SC_CT + (threadIdx.x & 31) * 16;
    const uint2 c1 = lds64(ct + 512);
    const uint4 c0 = lds128(ct);
    const uint32_t w0 = c0.x, w1 = c0.y, w2 = c0.z, w3 = c0.w, a0 = ut + c1.x, a1 = ut + c1.y;
#pragma unroll
    for (int j = 0; j < 8; j++) {
        const uint2 x = lds64(a0 + 128 * j - 16), y = lds64(a1 + 128 * j), z = lds64(a0 + 128 * j);
        float X[4], Y[4], Z[4];
        mma_bf0(X, w0, w1, w2, w3, x.x, x.y); mma_bf0(Y, w0, w1, w2, w3, y.x, y.y); mma_bf0(Z, w0, w1, w2, w3, z.x, z.y);
        q[j][0] = pack_bf16(Y[2], Y[3]); q[j][1] = pack_bf16(Z[2], Z[3]); q[j][2] = pack_bf16(X[0], X[1]); q[j][3] = pack_bf16(Y[0], Y[1]);
    }
}
template <int N>
__device__ __forceinline__ void kissue(const Params& p, int ch, uint4 (&x)[4]) {
    const uint4* src = p.scr->kx + ch * 128 + (threadIdx.x & 31);
#pragma unroll
    for (int i = 0; i < N; i++) x[i] = ld_pkt(src + 32 * i);
}
template <int N>
__device__ __forceinline__ void kfetch(const Params& p, int ch, uint32_t tag, uint4 (&x)[4]) {
    tag <<= 16;
    for (int it = 0; !__all_sync(0xffffffffu, ((x[0].w ^ tag) | (x[1].w ^ tag) | (x[2].w ^ tag) | (x[N - 1].w ^ tag)) < 0x10000u);) {
        kissue<N>(p, ch, x);
        POLL_GUARD(it);
    }
}
__device__ __forceinline__ void kpublish(const Params& p, int ch, uint32_t tag, uint4 (&x)[4]) {
    uint4* const dst = p.scr->kx + ch * 128 + (threadIdx.x & 31);
#pragma unroll
    for (int i = 0; i < 3; i++) { x[i].w |= tag << 16; st_pkt(dst + 32 * i, x[i].x, x[i].y, x[i].z, x[i].w); }
}

template <int LO, int HI>
__device__ __forceinline__ void conv_core(float (&acc)[16][4], uint32_t sb, int warp, uint32_t kt, uint32_t ut, uint32_t ct, uint32_t out) {
    const uint32_t oz = blockIdx.y;
    const uint2 c1 = lds64(ct + 520);
    uint4 c2;
    {
        uint32_t a[4][4], b[8][4];
        uint32_t k1 = kt + c1.y, u1 = ut + c1.x;
        constexpr int AM = LO ? AMODE_U : AMODE_H;
        auto lda = [&](int j1, bool first) {
            a[j1][2] = (AM & 1) && !first ? a[j1][1] + oz : lds32v(k1 + 512 * j1 - 32);
            a[j1][0] = lds32(k1 + 512 * j1); a[j1][1] = lds32(k1 + 512 * j1 + 32);
            a[j1][3] = (AM & 2) ? a[j1][0] + oz : lds32v(k1 + 512 * j1);
        };
        auto ldb = [&](int m2) { if (2 * m2 + 1 < HI) ldsm4(b[m2], u1 + 256 * m2); else ldsm2(b[m2], u1 + 256 * m2); };
        lda(0, true);
#pragma unroll
        for (int m2 = LO / 2; m2 < (HI + 1) / 2; m2++) ldb(m2);
#pragma unroll
        for (int i = 0; i < (LO ? 8 : 16); i++) acc[i][0] = acc[i][1] = acc[i][2] = acc[i][3] = 0.f;
#pragma unroll
        for (int j0 = 0; j0 < 8; j0++) {
            k1 += 64; u1 -= 16;
            lda(3, j0 == 0);
#pragma unroll
            for (int m = 0; m < HI; m++) {
                if (m >= LO) mma_bf(acc[m], a[0][0], a[0][1], a[0][2], a[0][3], b[m >> 1][2 * (m & 1)], b[m >> 1][2 * (m & 1) + 1]);
                if (((m & 1) || m == HI - 1) && (m + 3 >= LO || j0 == 7)) ldb(m >> 1);
            }
            lda(2, j0 == 0); lda(1, j0 == 0); lda(0, false);
#pragma unroll
            for (int j1 = 3; j1 > 0; j1--)
#pragma unroll
                for (int m = j0 == 7; m + j1 < HI; m++)
                    if (m + j1 >= LO) mma_bf(acc[m + j1 + (!LO && j1 >= SPLITJ && m + j1 >= SPLITM ? 8 : 0)], a[j1][0], a[j1][1], a[j1][2], a[j1][3], b[m >> 1][2 * (m & 1)], b[m >> 1][2 * (m & 1) + 1]);
        }
        if (!LO) {
#pragma unroll
            for (int i = SPLITM; i < HI; i++) { acc[i][0] += acc[i + 8][0]; acc[i][1] += acc[i + 8][1]; acc[i][2] += acc[i + 8][2]; acc[i][3] += acc[i + 8][3]; }
        }
        c2 = lds128(ct + 1024);
#pragma unroll
        for (int m = LO ? LO : 1; m < HI; m++) mma_bf(acc[m], a[0][0], a[0][1], a[0][2], a[0][3], b[m >> 1][2 * (m & 1)], b[m >> 1][2 * (m & 1) + 1]);
        if (HI > 8) {
            const uint32_t kv = __byte_perm(lds32(kt + KT_P4 + 140 * 4), 0, 0x1010), e0 = kv & c2.x, e1 = kv & c2.y;
            const uint32_t e3 = e0 + oz, e4 = e1 + oz, z2 = oz + oz;
            uint32_t f[2][4];
            ldsm4(f[0], ut + c2.w); ldsm4(f[1], ut + c2.w + 512);
#pragma unroll
            for (int m = 1; m < 9; m++) mma_bf(acc[m + 7], e0, e1, oz, e3, b[m >> 1][2 * (m & 1)], b[m >> 1][2 * (m & 1) + 1]);
#pragma unroll
            for (int m = 0; m < 8; m++) mma_bf8(acc[m + 8], e4, z2, f[m >> 2][m & 3]);
        }
    }
    if (LO) { }
    uint32_t kb[5][4];
#pragma unroll
    for (int l = 0; l < 5; l++) if (l + 3 < HI) { const uint4 x = lds128(kt + c2.z + 128 * l); kb[l][0] = x.x; kb[l][1] = x.y; kb[l][2] = x.z; kb[l][3] = x.w; }
    const uint4 c3 = lds128(ct + 1536), c4 = lds128(ct + 2048);
    const uint32_t w0 = c3.x, w1 = c3.y, w2 = c3.z, w3 = c3.w, a0 = ut + c4.x, a1 = ut + c4.y;
    auto emit = [&](int q) {
        const uint32_t y0 = pack_bf16(acc[2 * q][0], acc[2 * q][1]), y1 = pack_bf16(acc[2 * q][2], acc[2 * q][3]);
        const uint32_t y2 = pack_bf16(acc[2 * q + 1][0], acc[2 * q + 1][1]), y3 = pack_bf16(acc[2 * q + 1][2], acc[2 * q + 1][3]);
        if (LO) st_async128(c4.z + out + q * OUT_STAGE, y0, y1, y2, y3, c4.w + 8 * q);
        else stsm4t(out + 512 * q, y0, y1, y2, y3);
    };
    uint32_t x[12][4];
    auto load = [&](int j) { x[j][0] = lds32(a0 + 128 * j - 16); x[j][1] = lds32(a1 + 128 * j - 16); x[j][2] = lds32(a0 + 128 * j); x[j][3] = lds32(a1 + 128 * j); };
    {
        float Z[4] = {0.f, 0.f, 0.f, 0.f};
        mma_bf8(Z, w2, w3, lds32(a1 - 128));
        const uint32_t z5 = pack_bf16(Z[0], Z[1]);
#pragma unroll
        for (int l = 0; l < 5; l++) if (3 + l >= LO && 3 + l < HI) mma_bf8(acc[3 + l], oz * 3, z5, kb[l][0]);
    }
    if (HI > 4) load(0);
    if (HI > 5) load(1);
    if (!LO) { __syncwarp(); emit(0); emit(1); }
#pragma unroll
    for (int j = 0; j + 4 < HI; j++) {
        if (LO) {
            if (j == JBAR) bar_sync(2 + (warp & 3), 64);
            if (j + 2 < 11) load(j + 2);
            if (j == 10) load(11);
        }
        float X[4], Y[4], Z[4];
        mma_bf0(X, w0, w1, w2, w3, x[j][0], x[j][1]); mma_bf0(Y, w0, w1, w2, w3, x[j][1] + oz, x[j][2] + oz); mma_bf0(Z, w0, w1, w2, w3, x[j][2], x[j][3]);
        const uint32_t x5 = pack_bf16(X[0], X[1]), x3 = pack_bf16(X[2], X[3]), y5 = pack_bf16(Y[0], Y[1]), y3 = pack_bf16(Y[2], Y[3]), z5 = pack_bf16(Z[0], Z[1]), z3 = pack_bf16(Z[2], Z[3]);
        const uint32_t y3c = y3 + oz, y5c = y5 + oz;
#pragma unroll
        for (int l = 0; l < 5; l++) if (j + 4 + l < HI && j + 4 + l >= LO) mma_bf(acc[j + 4 + l], y5, z5, y3, z3, kb[l][0], kb[l][1]);
#pragma unroll
        for (int l = 0; l < 5; l++) if (j + 4 + l < HI && j + 4 + l >= LO) mma_bf(acc[j + 4 + l], x5, y5c, x3, y3c, kb[l][2], kb[l][3]);
        if (((j & 1) || j + 5 == HI) && j + 4 >= LO) emit(2 + (j >> 1));
    }
}

__device__ __forceinline__ void conv_warp(uint32_t sb, int warp, const uint32_t (&q)[8][4], uint4 k8) {
    const int lane = threadIdx.x & 31;
    const uint32_t kt = sb + SC_KT + warp * KT_BYTES;
    float acc[16][4];
    const uint32_t a8 = kt + KT_P8 + (6 + 32 * (lane & 3) + (lane >> 2)) * 4;
    sts32(a8, k8.x); sts32(a8 + 32, k8.y); sts32(a8 + 64, k8.z); sts32(a8 + 96, k8.w);
    __syncwarp();
#pragma unroll
    for (int l = 0; l < 8; l++) {
        const uint2 kb = lds64(kt + KT_P8 + (3 + 8 * l + (lane >> 2) - (lane & 3)) * 8);
#pragma unroll
        for (int j = 0; j < 8 - l; j++) {
            if (l == 0) mma_bf0(acc[8 + j], q[j][0], q[j][1], q[j][2], q[j][3], kb.x, kb.y);
            else mma_bf(acc[8 + j + l], q[j][0], q[j][1], q[j][2], q[j][3], kb.x, kb.y);
        }
    }
    asm volatile("setmaxnreg.inc.sync.aligned.u32 168;");
    if (warp < 4) { bar_sync(6 + warp, 64); mbar_wait(sb + SB_UT + 8); }
    conv_core<NL, 16>(acc, sb, warp, kt, sb + SC_UT + warp * UT_STRIDE + 128, sb + SC_CT + lane * 16, warp * 288);
}

__device__ __forceinline__ void conv_low(const Params& p, uint32_t sb, int slab, int warp, uint32_t t0, uint32_t tag, uint4 (&x)[4]) {
    const int lane = threadIdx.x & 31, g = lane >> 2, t = lane & 3, mi = lane >> 3, r8 = lane & 7;
    const uint32_t kt = sb + SH_KT + warp * KH_BYTES;
    mbar_wait(sb + FB_UT);
    if (lane < 11) sts128(kt + 16 * (lane < 4 ? lane : 128 + lane), 0, 0, 0, 0);
    __syncwarp();
    const int row0 = 32 * (warp >> 1) + 16 * (t >> 1) + 8 * (warp & 1) + g;
    uint32_t r[NL] = {t0 + (warp < 4 ? KDELAY1 : KDELAY2)};
    if (warp < 4) while (clk() - t0 < KDELAY0) __nanosleep(100);
#pragma unroll 1
    for (int c = warp;; c ^= 12) {
        kfetch<3>(p, 16 * slab + c, tag, x);
        kstore(x, kt);
        x[1].w = 0;
        if (c >= 8) {
#pragma unroll
            for (int i = 0; i < NL; i++) r[i] = ld_rlx32(&p.scr->rec[row0 + 128 * i]);
        } else if ((int)(clk() - r[0]) >= 0) kissue<3>(p, 16 * slab + (c ^ 12), x);
        __syncwarp();
        float acc[16][4];
        conv_core<0, NL>(acc, sb, warp, kt, sb + SH_UT + c * UH_STRIDE + 4 * (c & 8) + 128, sb + SH_CT + lane * 16, (c < 8 ? sb + SH_OUT + c * OH_STRIDE : kt + 32) + lane * 16);
        if (c >= 8) break;
    }
    for (int it = 0;;) {
        uint32_t bad = 0;
#pragma unroll
        for (int i = 0; i < NL; i++) bad |= r[i] ^ (tag << 14);
        if ((bad & 0xc000u) == 0) break;
#pragma unroll
        for (int i = 0; i < NL; i++) r[i] = ld_rlx32(&p.scr->rec[row0 + 128 * i]);
        POLL_GUARD(it);
    }
    __syncwarp();
    mbar_wait(sb + FB_X);
    const uint32_t thr = key_thr(lds32(sb + SF_SEL + 28));
    const int cl = 2 * mi + (r8 & 1), un = 32 * (warp >> 1) + 16 * (r8 >> 2);
    const uint32_t ua = sb + SH_UT + cl * UH_STRIDE + ((r8 & 2) ? UH_HI : 0) + 128 + (warp & 1) * UH_PL + un;
    const uint32_t ya = sb + ((r8 & 2) ? SH_KT + 32 + (cl ^ 4) * KH_BYTES : SH_OUT + cl * OH_STRIDE) + (warp & 1) * 128 + un;
    uint32_t gg[NL], o[NL][4], routed = 0;
#pragma unroll
    for (int i = 0; i < NL; i++) {
        ldsm4t(o[i], ua + 128 * i);
        gg[i] = __byte_perm(r[i], 0, 0x1010) & 0x3fff3fffu;
        uint32_t om = hsub2(0x3f803f80u, gg[i]);
        if (((r[i] & 0xffff0000u) | (uint32_t)(2047 - 128 * i - row0)) >= thr) { om = 0; routed |= 1 << i; }
#pragma unroll
        for (int k = 0; k < 4; k++) o[i][k] = hmul2(om, o[i][k]);
    }
    __nv_bfloat16* const op = p.out + row0 * DM + 16 * slab + 8 * (t & 1);
    if (routed) for (int it = 0; ld_acq32(&p.scr->zero[8 * (2 * slab + (warp >> 2))]) != tag;) POLL_GUARD(it);
    __syncwarp();
    bar_sync(13, 448);
#pragma unroll
    for (int i = 0; i < NL; i++) {
        uint32_t y[4];
        ldsm4t(y, ya + 256 * i);
#pragma unroll
        for (int k = 0; k < 4; k++) o[i][k] = hfma2(gg[i], y[k], o[i][k]);
        asm volatile("{ .reg .pred p; setp.ne.u32 p, %5, 0; @p red.relaxed.gpu.global.add.noftz.v4.bf16x2 [%0], {%1, %2, %3, %4}; @!p st.global.v4.b32 [%0], {%1, %2, %3, %4}; }"
                     :: "l"(op + 128 * i * DM), "r"(o[i][0]), "r"(o[i][1]), "r"(o[i][2]), "r"(o[i][3]), "r"(routed & (1 << i)) : "memory");
    }
}

__device__ __forceinline__ uint32_t utile_addr(uint32_t sb, int row, int c8) {
    return sb + SC_UTILE + (row >> 9) * 8192 + (((row >> 4) & 3) + 4 * (row & 1) + 8 * ((row >> 7) & 3) + 32 * ((row >> 1) & 7)) * 32 + ((c8 ^ row) & 1) * 16;
}

__device__ __forceinline__ void conv_helper(const Params& p, const CUtensorMap* mU, uint32_t sb, int cb, int hw, uint32_t t0) {
    const int lane = threadIdx.x & 31, g = lane >> 2, t = lane & 3, mi = lane >> 3, r8 = lane & 7;
    const int rank = cb & 1, slab = cb >> 1;
    const uint32_t bar_out = sb + SB_OUT, s_key = sb + SC_KEY;
    asm volatile("setmaxnreg.dec.sync.aligned.u32 88;");
    uint32_t tag = 0;
    if (elect()) {
        const uint32_t b = sb + SC_BAR + 8 * hw;
        mbar_init(b, hw < 4 ? 1 : 9); mbar_init(bar_out + 8 * hw, 1);
        mbar_fence_init();
        if (hw < 6) mbar_expect(b, 8192);
        if (hw < 4) {
            if (hw >= 2) spin_until(t0, VDELAY);
            tma5d(sb + SC_UTILE + hw * 8192, mU, 16 * slab, 4 * rank, 0, 4 * hw, 0, b);
        }
        mbar_expect(bar_out + 8 * hw, 4096);
        if (hw == 4) tag = take_ticket(&p.scr->launch);
    }
    __syncwarp();
    cluster_arrive_relaxed();
    if (lane < 16) sts128(sb + SC_UT + hw * UT_STRIDE + mi * UT_PL + r8 * 16, 0, 0, 0, 0);
    if (lane < 17) sts128(sb + SC_KT + hw * KT_BYTES + 16 * (lane < 4 ? lane : lane < 11 ? 128 + lane : 164 + lane), 0, 0, 0, 0);
    if (hw == 7) conv_consts<UT_PL>(sb + SC_CT, sb + SC_OUT + rank * OUT_HALF, bar_out);
    if (hw == 4) { tag = tag_of(__reduce_max_sync(0xffffffffu, tag)); sts32(sb + SC_TAG, tag); }
    cluster_wait();
    {
        const int box = hw >> 2, h = hw & 1, k0 = hw & 2;
        const uint32_t src = sb + SC_UTILE + box * 8192 + h * 4096 + k0 * 256 + (32 * mi + (r8 >> 1) + 4 * (r8 & 1)) * 32;
        const uint32_t so = ((rank ^ r8) & 1) << 4;
        const uint32_t dst = sb + SC_UT + g * UT_STRIDE + 128 + h * UT_PL + k0 * 128 + (32 * box + 4 * rank + t) * 16;
        const uint32_t rdst = mapa(dst, rank ^ 1), rbar = mapa(sb + SB_UT, rank ^ 1);
#pragma unroll 1
        for (int i = 0; i < 2; i++) {
            mbar_wait(sb + SC_BAR + 8 * box + 16 * i);
            const uint32_t ts = clk();
            uint32_t a[2][4], b[2][4];
#pragma unroll
            for (int k = 0; k < 2; k++) { ldsm4t(a[k], src + (so ^ 16) + k * 256 + i * 16384); ldsm4t(b[k], src + so + k * 256 + i * 16384); }
#pragma unroll
            for (int k = 0; k < 2; k++) sts128(dst + k * 128 + i * 1024, b[k][0], b[k][1], b[k][2], b[k][3]);
#pragma unroll
            for (int k = 0; k < 2; k++) {
                if (k == 0) { __syncwarp(); if (lane == 0) mbar_arrive(sb + SB_UT + 8 * i); }
                spin_until(ts, (hw + 8 * k) * PACE);
                st_async128(rdst + k * 128 + i * 1024, a[k][0], a[k][1], a[k][2], a[k][3], rbar + 8 * i);
            }
        }
    }
    if (hw > 4) {
        bar_arrive(1, 256);
        if (hw == 5) {
            uint32_t tn = t0 + WDELAY + 3 * WPER0 + 6 * WPER;
            const int q = 72 * lane + cb, i = q / 120, r = q % 120, od = (i < 4 ? 4 * (r & ~3) + 4 * i + (r & 3) : q) * 4608;
#pragma unroll 1
            for (int n = 0; n < 8; n++, tn += DPER) {
                const int o = __shfl_sync(0xffffffffu, od, n);
                while ((int)(clk() - tn) < 0) __nanosleep(20);
                if (elect()) prefetch_l2(p.wd + o, 9216);
            }
        }
        return;
    }
    if (hw == 4) {
        uint32_t key;
        while (clk() - t0 < SDELAY) __nanosleep(400);
        for (int it = 0;;) {
            key = ld_rlx32(&p.scr->sel[g]);
            if (__all_sync(0xffffffffu, key >> 29 == tag)) break;
            POLL_GUARD(it);
            __nanosleep(200);
        }
        if (lane == 31) sts32(s_key, key);
        bar_arrive(1, 256);
        const int row = key_row(key);
        const bool own = ((row >> 6) & 1) == rank;
        uint32_t* const op = (uint32_t*)(p.out + row * DM + 16 * slab) + 2 * t;
        if (own) asm volatile("st.relaxed.gpu.global.v2.b32 [%0], {%1, %1};" :: "l"(op), "r"(0) : "memory");
        uint32_t rc;
        for (int it = 0;;) { rc = ld_rlx32(&p.scr->rec[row]); if (((rc >> 14) & 3u) == tag) break; POLL_GUARD(it); }
        __syncwarp();
        asm volatile("fence.acq_rel.gpu;" ::: "memory");
        if (lane < 8) st_rlx32(&p.scr->zero[8 * cb + lane], tag);
        if (own && row >= 128 * NL) {
            const uint32_t gg = __byte_perm(rc, 0, 0x1010) & 0x3fff3fffu;
            const uint32_t ya = sb + SC_OUT + (row >> 8) * OUT_STAGE + (t >> 1) * OUT_HALF + (t & 1) * 1152 + (row & 7) * 32 + ((row >> 5) & 1) * 16
                                + ((row >> 7) & 1) * 8 + ((row >> 3) & 1) * 4 + ((row >> 4) & 1) * 2;
            mbar_wait(bar_out + 8 * (row >> 8));
            const uint32_t y0 = lds16(ya) | (lds16(ya + 288) << 16), y1 = lds16(ya + 576) | (lds16(ya + 864) << 16);
            red_bf2(op, hmul2(gg, y0)); red_bf2(op + 1, hmul2(gg, y1));
        }
        return;
    }
    bar_sync(1, 256);
    {
        const uint32_t last = lds32(s_key), tg = last >> 29 << 14;
        const int par = hw >> 1, i0 = 4 * (hw & 1);
        const int row0 = 256 * par + 128 * (g >> 2) + 64 * rank + 32 * (t >> 1) + 16 * (g & 1) + 8 * ((g >> 1) & 1) + i0;
        uint4 r[4];
        for (int it = 0;;) {
            uint32_t bad = 0;
#pragma unroll
            for (int k = NL / 4; k < 4; k++) { r[k] = ld_rlx128(&p.scr->rec[row0 + 512 * k]); }
#pragma unroll
            for (int k = NL / 4; k < 4; k++) bad |= (r[k].x ^ tg) | (r[k].y ^ tg) | (r[k].z ^ tg) | (r[k].w ^ tg);
            if ((bad & 0xc000u) == 0) break;
            POLL_GUARD(it);
        }
        const uint32_t thr = key_thr(last);
        const uint32_t ya = sb + SC_OUT + par * OUT_STAGE + ((r8 >> 1) & 1) * OUT_HALF + (2 * mi + (r8 & 1)) * 288 + (2 * i0 + (r8 >> 2)) * 16;
        const uint32_t ua = utile_addr(sb, row0, t & 1);
        __nv_bfloat16* op = p.out + row0 * DM + 16 * slab + 8 * (t & 1);
#pragma unroll
        for (int k = NL / 4; k < 4; k++) {
            if (4 * k + 1 < NL && par == 0) continue;
            const uint32_t rr[4] = {r[k].x, r[k].y, r[k].z, r[k].w};
            uint4 ou[4];
            uint32_t gg[4];
#pragma unroll
            for (int i = 0; i < 4; i++) {
                gg[i] = __byte_perm(rr[i], 0, 0x1010) & 0x3fff3fffu;
                const uint32_t om = hsub2(0x3f803f80u, gg[i]);
                const uint4 u4 = lds128((ua ^ ((i & 1) * 16)) + k * 8192 + (i & 1) * 128 + (i >> 1) * 1024);
                ou[i] = make_uint4(hmul2(om, u4.x), hmul2(om, u4.y), hmul2(om, u4.z), hmul2(om, u4.w));
            }
            mbar_wait(bar_out + 8 * par + 16 * k);
            uint32_t y[4][4];
#pragma unroll
            for (int i = 0; i < 4; i++) ldsm4t(y[i], ya + 2 * k * OUT_STAGE + 32 * i);
#pragma unroll
            for (int i = 0; i < 4; i++) {
                const uint4 o = make_uint4(hfma2(gg[i], y[i][0], ou[i].x), hfma2(gg[i], y[i][1], ou[i].y), hfma2(gg[i], y[i][2], ou[i].z), hfma2(gg[i], y[i][3], ou[i].w));
                if (((rr[i] & 0xffff0000u) | (uint32_t)(2047 - 512 * k - i - row0)) < thr && (!(NL & 1) || row0 + 512 * k >= 128 * NL)) *(uint4*)(op + (512 * k + i) * DM) = o;
            }
        }
    }
}

struct Maps { const CUtensorMap *U2, *R, *G64, *U64, *G32, *U32, *Wd; };

__device__ __forceinline__ void load_weights(const Params& p, const Maps& m, uint32_t sb, int f, bool pure, int n, int n1, uint32_t& tn) {
#pragma unroll 1
    for (; n < n1; n++) {
        const uint32_t b = sb + FB_W + 8 * n, d = sb + n * (pure ? PIECE_P : PIECE_H);
        if (n >= (pure ? 3 : 4)) mbar_wait(n < 4 ? sb + FB_SEL : n < 9 ? sb + FB_KG : b + FB_FREE - FB_D);
        while ((int)(clk() - tn) < 0) __nanosleep(30);
        tn += n < 3 ? WPER0 : n < 9 ? WPER : DPER * 5 / 3;
        __syncwarp();
        if (elect()) {
            if (n == 9) mbar_arrive_peer(mapa(sb + FB_PEER, 1));
            if (n >= 9) tma3d(d - 9 * PIECE_P, m.Wd, 0, n < 13 ? 64 * f + 32 * n - 288 : 16 * f + 3840, 0, b);
            else {
                tma2d(d, m.G64, 64 * f, 64 * n, b); tma2d(d + 8192, m.U64, 64 * f, 64 * n, b);
                if (pure) { tma2d(d + 16384, m.G32, 3840 + 16 * f, 64 * n, b); tma2d(d + 20480, m.U32, 3840 + 16 * f, 64 * n, b); }
            }
        }
    }
}

__device__ __forceinline__ void above(uint4 x, uint32_t m, uint32_t& a, uint32_t& b) {
    asm("{ .reg .u32 p, q, r, s; mad.lo.u32 p, %2, -1, %6; mad.lo.u32 q, %3, -1, %6; mad.lo.u32 r, %4, -1, %6; mad.lo.u32 s, %5, -1, %6;"
        "shr.u32 p, p, 31; shr.u32 q, q, 31; shr.u32 r, r, 31; shr.u32 s, s, 31; add.u32 %0, %0, p; add.u32 %1, %1, q; add.u32 %0, %0, r; add.u32 %1, %1, s; }"
        : "+r"(a), "+r"(b) : "r"(x.x), "r"(x.y), "r"(x.z), "r"(x.w), "r"(m));
}
__device__ __forceinline__ void select_rows(const Params& p, uint32_t sb, int f, int sw, uint32_t tag, uint32_t t0) {
    const int lane = threadIdx.x & 31, tid = 32 * sw + lane;
    uint4 k[6];
    uint32_t qm[6];
    const uint32_t ca = sb + SF_CNT + (lane & blockIdx.y);
    tag <<= 29;
    k[5] = make_uint4(tag, tag, tag, tag);
    sts128(sb + SF_LIST + tid * 16, 0, 0, 0, 0); sts128(sb + SF_LIST + 1536 + tid * 16, 0, 0, 0, 0); sts128(sb + SF_LIST + 2560 + tid * 16, 0, 0, 0, 0);
    while (clk() - t0 < PDELAY) __nanosleep(40);
    bool bad[6] = {true, true, true, true, true, sw == 0};
    for (int it = 0;;) {
#pragma unroll
        for (int i = 0; i < 6; i++) if (bad[i]) k[i] = ld_rlx128(&p.scr->rec[L_SEQ + 384 * i + 4 * tid]);
#pragma unroll
        for (int i = 0; i < 6; i++) {
            qm[i] = max(__vimax3_u32(k[i].x, k[i].y, k[i].z), k[i].w);
            bad[i] = ((min(__vimin3_u32(k[i].x, k[i].y, k[i].z), k[i].w) ^ tag) | (qm[i] ^ tag)) >= 0x20000000u;
        }
        if (!__any_sync(0xffffffffu, bad[0] | bad[1] | bad[2] | bad[3] | bad[4] | bad[5])) break;
        POLL_GUARD(it);
    }
    {
        uint32_t mx[6];
#pragma unroll
        for (int i = 0; i < 6; i++) mx[i] = __reduce_max_sync(0xffffffffu, qm[i]);
        sts128(sb + SF_MAX + 16 * sw, mx[0], mx[1], mx[2], mx[3]); sts32(sb + SF_MAX + 48 + 4 * sw, mx[4]);
        if (sw == 0) sts32(sb + SF_MAX + 60, mx[5]);
    }
    bar_sync(8, 96);
    uint32_t thr;
    {
        const uint32_t m = lds32(sb + SF_MAX + (lane & 15) * 4);
        const uint4 x = lds128(sb + SF_MAX + 2 * (lane & 16)), y = lds128(sb + SF_MAX + 2 * (lane & 16) + 16);
        uint32_t rk = 0, r2 = 0;
        above(x, m, rk, r2); above(y, m, rk, r2);
        rk += r2;
        thr = __reduce_max_sync(0xffffffffu, rk + __shfl_xor_sync(0xffffffffu, rk, 16) == 7 ? m : 0u);
    }
    uint32_t pos = 0;
    uint32_t cnt = (thr - 1 - qm[4]) >> 31, c2 = (thr - 1 - qm[5]) >> 31;
    above(make_uint4(qm[0], qm[1], qm[2], qm[3]), thr - 1, cnt, c2);
    cnt = 16 * (cnt + c2);
    asm volatile("{ .reg .pred p; setp.ne.u32 p, %2, 0; @p atom.shared.add.u32 %0, [%1], %2; }" : "+r"(pos) : "r"(ca), "r"(cnt) : "memory");
#pragma unroll
    for (int i = 0; i < 6; i++) if (qm[i] >= thr) { sts128(sb + SF_LIST + pos, k[i].x, k[i].y, k[i].z, k[i].w); pos += 16; }
    bar_sync(8, 96);
    const int n = lds32(sb + SF_CNT);
    uint32_t m, rk;
    int base = 0;
#pragma unroll 1
    do {
        m = lds32(sb + SF_LIST + base + 12 * (lane & 28) + 16 * sw + 4 * (lane & 3));
        rk = 0;
        uint32_t r2 = 0;
        int i = 0;
#pragma unroll 1
        do {
            uint4 x[6];
#pragma unroll
            for (int e = 0; e < 6; e++) x[e] = lds128(sb + SF_LIST + i + 16 * e);
#pragma unroll
            for (int e = 0; e < 6; e++) above(x[e], m, rk, r2);
        } while ((i += 16 * 6) < n);
        rk += r2;
        if (rk < 8) sts32(sb + SF_SEL + 4 * rk, m);
    } while ((base += 384) < n);
    if (RARE(n > 384)) {
        bar_sync(8, 96);
        rk = tid; m = lds32(sb + SF_SEL + 4 * (lane & 7));
    }
    if (rk < 8) {
        mbar_expect(sb + FB_X, 1152);
        bulk_load(sb + SF_XS + 1168 * rk, p.u + key_row(m) * DM, 1152, sb + FB_X);
        if (f == 0) st_rlx32(&p.scr->sel[rk], m);
    }
    __syncwarp();
}

__device__ __forceinline__ void ffn_worker(const Params& p, const Maps& m, uint32_t sb, int f, bool pure, int gw, uint32_t t0, uint32_t tag, uint32_t tn) {
    const int lane = threadIdx.x & 31, mi = lane >> 3, r8 = lane & 7, kr = 8 * (mi >> 1) + r8, np = pure ? 6 : 4, kh = gw >= np, j = gw - kh * np;
    const uint32_t sh = sb + (pure ? SP_H : SH_H);
    uint4* const pdst = p.scr->part + ((12 * (f & 1) + 2 * gw) * 30 + (f >> 1)) * 32 + lane;
    {
        const int cc = 2 * j + (mi & 1), piece = pure ? PIECE_P : PIECE_H;
        const uint32_t ws = j < 4 ? 2048 : 1024, xa = sb + SF_XS + r8 * 1168 + mi * 16 + kh * 64;
        const uint32_t wa = (j < 4 ? sb + kr * 128 + ((cc ^ r8) << 4) : sb + 16384 + kr * 64 + (((cc ^ (r8 >> 1)) & 3) << 4)) + 2 * kh * ws;
        uint32_t a[9][4][4];
        auto fetch = [&](int n) {
            mbar_wait(sb + FB_W + 8 * n);
#pragma unroll
            for (int s = 0; s < 4; s++) ldsm4t(a[n][s], wa + n * piece + ((s & 1) + 4 * (s >> 1)) * ws);
        };
        auto release = [&](int n) {
            asm volatile("" :: "r"(a[n][0][0]), "r"(a[n][1][0]), "r"(a[n][2][0]), "r"(a[n][3][0]) : "memory");
            __syncwarp();
            if (lane == 0) mbar_arrive(sb + FB_FREE + 8 * n);
        };
        fetch(0); fetch(1); release(0); fetch(2); release(1); fetch(3); release(2);
        fetch(4); release(3); fetch(5); release(4); release(5);
        if (!pure && gw == 5) {
            mbar_wait(sb + FB_FREE + 40);
            while ((int)(clk() - tn) < 0) __nanosleep(30);
            __syncwarp();
            if (elect()) {
                for (int i = 0; i < 4; i++) tma3d(sb + i * DPIECE, m.Wd, 0, 64 * (f & ~1) + 32 * i, 9 * (f & 1), sb + FB_D + 8 * i);
                if (f < 48) tma3d(sb + 4 * DPIECE, m.Wd, 0, 16 * f + 3824, 9, sb + FB_D + 32);
            }
        }
        mbar_wait(sb + FB_X);
        float c[4][4] = {};
#pragma unroll
        for (int n = 0; n < 9; n++) {
            uint32_t x[4];
            ldsm4(x, xa + 128 * n);
            if (n >= 2 && n < 5) fetch(n + 4);
            if (n >= 7 && gw < 6) st_pkt(pdst + (n - 7) * 30 * 32, 0, 0, 0, 0);
#pragma unroll
            for (int s = 0; s < 4; s++) mma_bf(c[s], a[n][2 * (s & 1) + (s >> 1)][0], a[n][2 * (s & 1) + (s >> 1)][1], a[n][2 * (s & 1) + (s >> 1)][2], a[n][2 * (s & 1) + (s >> 1)][3], x[s & 2], x[(s & 2) + 1]);
        }
        for (int i = 0; i < 8; i++) c[i >> 2][i & 3] += c[2 + (i >> 2)][i & 3];
        mbar_wait(sb + FB_FREE + 40);
        const uint32_t ex = sb + (pure ? SP_EX : 5 * DPIECE) + lane * 16;
        sts128(ex + gw * 512, __float_as_uint(kh ? c[0][0] : c[0][2]), __float_as_uint(kh ? c[0][1] : c[0][3]), __float_as_uint(kh ? c[1][0] : c[1][2]), __float_as_uint(kh ? c[1][1] : c[1][3]));
        bar_sync(2 + j, 64);
        const uint4 o = lds128(ex + (kh ? j : gw + np) * 512);
        const float g0 = rbf((kh ? c[0][2] : c[0][0]) + __uint_as_float(o.x)), g1 = rbf((kh ? c[0][3] : c[0][1]) + __uint_as_float(o.y));
        const float u0 = rbf((kh ? c[1][2] : c[1][0]) + __uint_as_float(o.z)), u1 = rbf((kh ? c[1][3] : c[1][1]) + __uint_as_float(o.w));
        uint32_t hp = pack_bf16(rbf(g0 * sigmoidf_(g0)) * u0, rbf(g1 * sigmoidf_(g1)) * u1);
        asm volatile("movmatrix.sync.aligned.m8n8.trans.b16 %0, %0;" : "+r"(hp));
        const uint32_t ho = (j + 4 * ((f & 1) | (j >> 2))) * 256 + lane * 8 + kh * 4;
        const bool pp = f < 48 && !pure;
        if (pp) mbar_wait(sb + FB_PEER);
        st_async32(mapa(sb + (pp ? SP_H : SH_H) + ho, ~f & 1), hp, mapa(sb + FB_GU, ~f & 1));
        sts32(sh + ho, hp);
        __syncwarp();
        if (lane == 0) mbar_arrive(sb + FB_GU);
    }
    if (gw < 6) {
        uint32_t off[3], w[2][6][4];
#pragma unroll
        for (int k = 0; k < 3; k++) off[k] = sb + ((3 * gw + k) >> 1) * 2048 + kr * 64 + ((((2 * (gw + k) + (mi & 1)) ^ (r8 >> 1)) & 3) << 4);
        float d[6][4] = {};
        auto dfetch = [&](int i) {
            mbar_wait(sb + FB_D + 8 * i);
#pragma unroll
            for (int k = 0; k < 6; k++) ldsm4t(w[i & 1][k], off[k % 3] + k / 3 * 1024 + i * (pure ? PIECE_P : DPIECE));
        };
        uint2 hv[10];
        auto dmult = [&](int i) {
#pragma unroll
            for (int k = 0; k < 6; k++) mma_bf(d[k], w[i & 1][k][0], w[i & 1][k][1], w[i & 1][k][2], w[i & 1][k][3], hv[2 * i + k / 3].x, hv[2 * i + k / 3].y);
        };
        dfetch(0); dfetch(1);
        mbar_wait(sb + FB_GU);
#pragma unroll
        for (int i = 0; i < 10; i++) hv[i] = lds64(sh + lane * 8 + i * 256);
        dmult(0); dfetch(2); dmult(1); dfetch(3); dmult(2);
        if (f < 48) { dfetch(4); dmult(3); dmult(4); } else dmult(3);
        auto word = [&](int k) { return pack_bf16(d[k >> 1][2 * (k & 1)] + d[3 + (k >> 1)][2 * (k & 1)], d[k >> 1][2 * (k & 1) + 1] + d[3 + (k >> 1)][2 * (k & 1) + 1]); };
#pragma unroll
        for (int k = 0; k < 2; k++) st_pkt(pdst + k * 30 * 32, word(3 * k), word(3 * k + 1), word(3 * k + 2), tag);
        bar_arrive(13, pure ? 384 : 448);
        return;
    }
    if (!pure) return;
    const uint4* src = p.scr->part + ((f >> 1) * 30 + 5 * gw - 30) * 32 + lane;
    bar_sync(13, 384);
    if (GDELAY) spin_until(clk(), GDELAY);
    uint4 v[5] = {};
    for (int it = 0;;) {
#pragma unroll
        for (int k = 0; k < 5; k++) if (v[k].w != tag) v[k] = ld_pkt(src + k * 32);
        if (((v[0].w ^ tag) | (v[1].w ^ tag) | (v[2].w ^ tag) | (v[3].w ^ tag) | (v[4].w ^ tag)) == 0) break;
        POLL_GUARD(it);
    }
    float s[6] = {};
#pragma unroll
    for (int k = 0; k < 5; k++) { s[0] += bf_lo(v[k].x); s[1] += bf_hi(v[k].x); s[2] += bf_lo(v[k].y); s[3] += bf_hi(v[k].y); s[4] += bf_lo(v[k].z); s[5] += bf_hi(v[k].z); }
#pragma unroll
    for (int k = 0; k < 3; k++) sts64(sb + SP_RED + gw * 768 + k * 256 + lane * 8, __float_as_uint(s[2 * k]), __float_as_uint(s[2 * k + 1]));
    __syncwarp();
    bar_arrive(12, 288);
}

__device__ __forceinline__ void ffn_cta(const Params& p, const Maps& m, uint32_t sb, int f, bool pure, int idx, int warp, uint32_t t0, uint4 (&x)[4], int ch) {
    const int lane = threadIdx.x & 31, g = lane >> 2, t = lane & 3, mi = lane >> 3, r8 = lane & 7;
    const int nw = pure ? 12 : 8, ng = pure ? 3 : idx < 4 ? 6 : 5;
    uint32_t tag = 0, tn = t0 + WDELAY;
    if (warp == 13) {
        if (elect()) {
            mbar_init(sb + FB_WR, 1);
            mbar_fence_init();
            mbar_expect(sb + FB_WR, 2304);
            bulk_load(sb + SF_WR, p.wr, 1152, sb + FB_WR); bulk_load(sb + SF_WR + 1152, p.gatew, 1152, sb + FB_WR);
            mbar_init(sb + FB_TK, 1);
#pragma unroll
            for (int i = 0; i < 14; i++) mbar_init(sb + FB_W + 8 * i, 1);
#pragma unroll
            for (int i = 0; i < 6; i++) mbar_init(sb + FB_FREE + 8 * i, nw);
            mbar_init(sb + FB_SEL, ng); mbar_init(sb + FB_KG, nw + ng); mbar_init(sb + FB_UT, 4); mbar_init(sb + FB_GU, nw + 1); mbar_init(sb + FB_PEER, 1); mbar_init(sb + FB_X, 8);
            mbar_fence_init();
        }
        __syncwarp();
        cluster_arrive_relaxed();
        if (elect()) { prefetch_map(m.G64); prefetch_map(m.U64); prefetch_map(m.G32); prefetch_map(m.U32); prefetch_map(m.Wd); }
        if (lane < 15) mbar_expect(sb + (lane < 14 ? FB_W + 8 * lane : FB_GU), lane < 9 ? (pure ? PIECE_P : PIECE_H) : lane < 14 ? DPIECE : f < 48 && !pure ? 1536 : 1024);
        __syncwarp();
        load_weights(p, m, sb, f, pure, 0, pure ? 14 : 9, tn);
        if (pure) return;
        mbar_wait(sb + FB_TK);
        tag = lds32(sb + SF_TK);
    } else if (warp >= nw) {
        const int r0 = pure ? 24 * idx : 576 + 40 * idx + 8 * min(idx, 4);
        const int grp = warp == 12 ? 0 : warp > 12 ? warp - 13 : warp - 5;
        const uint32_t rows = sb + (pure ? SP_R : grp < 5 ? SH_R : SH_R5 - 5 * 9216) + grp * 9216, bar_r = sb + FB_R + 8 * grp;
        const int i = 32 * grp + lane;
        if (elect()) {
            mbar_init(bar_r, 1); mbar_fence_init(); mbar_expect(bar_r, grp < 6 ? 9216 : NL * 4096);
            if (grp < ng) { spin_until(t0, RDELAY); tma3d(rows, m.R, 0, r0 + 8 * grp, 0, bar_r); }
        }
        __syncwarp();
        cluster_arrive_relaxed();
        if (i == 0) tag = take_ticket(&p.scr->launch);
        uint32_t* rp = &p.scr->rec[r0 + 8 * grp + g + L_SEQ * (t ^ 1)];
        uint32_t wa = sb + SF_WR + ((r8 >> 1) & 1) * 1152 + (2 * mi + (r8 & 1)) * 16, ra = rows + r8 * 128 + ((mi ^ r8) << 4), ts = t ? 14 : 29, kb = t ? 0 : 2047 - r0 - 8 * grp - g;
        asm volatile("" : "+l"(rp), "+r"(wa), "+r"(ra), "+r"(ts), "+r"(kb));
        if (grp < ng && t < 2) st_rlx32(rp, 0);
        if (f == 0 && i >= 88) st_rlx32(&p.scr->sel[r8], 0);
        if (grp == 6) {
            conv_consts<UH_PL>(sb + SH_CT, sb, sb);
            while (clk() - t0 < HDELAY) __nanosleep(50);
            if (elect()) { tma5d(sb + SH_RAW, m.U2, 16 * idx, 0, 0, 0, 0, bar_r); tma5d(sb + SH_RAW + NL * 2048, m.U2, 16 * idx, 4, 0, 0, 0, bar_r); }
        }
        __syncwarp();
        cluster_wait();
        if (grp < ng) {
            mbar_wait(sb + FB_WR);
            uint32_t wv[9][4];
#pragma unroll
            for (int k = 0; k < 9; k++) ldsm4(wv[k], wa + 128 * k);
            float c[3][4];
            const uint32_t rb2 = ra ^ 64;
            if (i == 0) { sts64(sb + SF_CNT, 0, tag_of(tag)); mbar_arrive(sb + FB_TK); }
            __syncwarp();
            mbar_wait(bar_r);
#pragma unroll
            for (int k = 0; k < 18; k++) {
                uint32_t a[4];
                ldsm4(a, ((k & 1) ? rb2 : ra) + (k >> 1) * 1024);
                if (k < 3) mma_bf0(c[k], a[0], a[1], a[2], a[3], wv[k >> 1][2 * (k & 1)], wv[k >> 1][2 * (k & 1) + 1]);
                else mma_bf(c[k % 3], a[0], a[1], a[2], a[3], wv[k >> 1][2 * (k & 1)], wv[k >> 1][2 * (k & 1) + 1]);
            }
            mbar_wait(sb + FB_TK);
            tag = lds32(sb + SF_TK);
            kb |= tag << ts;
            const float s = (c[0][0] + c[0][3]) + (c[1][0] + c[1][3]) + (c[2][0] + c[2][3]);
            const uint32_t sr = pack_bf16(0.f, s), rb = sr ^ ((((int)sr >> 31) & 0x7fff0000u) | 0x80000000u);
            if (ts == 29) st_rlx32(rp, (rb >> 3) | kb);
            const uint32_t rec = __shfl_up_sync(0xffffffffu, rb, 1) | kb | (pack_bf16(sigmoidf_(bf_hi(sr)), 0.f) & 0x3fffu);
            if (t == 1) st_rlx32(rp, rec);
            if (lane == 0) { mbar_arrive(sb + FB_SEL); mbar_arrive(sb + FB_KG); }
        }
        if (warp >= 12) select_rows(p, sb, f, grp, tag, t0);
        else {
            const int r = warp & 1, h = (warp >> 1) & 1;
            const uint32_t src = sb + SH_RAW + r * NL * 2048 + (8 * NL * (4 * h + mi) + (r8 >> 1) + 4 * (r8 & 1)) * 32 + (r8 & 1) * 16;
            const uint32_t dst = sb + SH_UT + g * UH_STRIDE + 128 + h * UH_PL + (4 * r + t) * 16;
            uint32_t a[2 * NL][4];
            mbar_wait(sb + FB_TK);
            tag = lds32(sb + SF_TK);
            mbar_wait(sb + FB_RAW);
#pragma unroll
            for (int k = 0; k < 2 * NL; k++) ldsm4t(a[k], (src ^ (16 * (k & 1))) + (k >> 1) * 256);
            mbar_wait(sb + FB_SEL);
#pragma unroll
            for (int k = 0; k < 2 * NL; k++) sts128(dst + (k & 1) * UH_HI + (k >> 1) * 128, a[k][0], a[k][1], a[k][2], a[k][3]);
            sts128(dst - 128, 0, 0, 0, 0); sts128(dst - 128 + UH_HI, 0, 0, 0, 0);
            __syncwarp();
            if (lane == 0) mbar_arrive(sb + FB_UT);
        }
    } else {
        mbar_wait(sb + FB_TK);
        tag = lds32(sb + SF_TK);
        if (warp < nw / 2) st_pkt(p.scr->kx + ch * 128 + 96 + lane, x[3].x, x[3].y, x[3].z, __byte_perm(x[3].w, tag, 0x5410));
        else kpublish(p, ch, tag, x);
        if (!pure) { conv_low(p, sb, idx, warp, t0, tag, x); return; }
    }
    if (pure && warp >= 12) {
            const int i = 32 * max(warp - 13, 0) + lane, col = 24 * idx + 2 * (i >> 3);
            mbar_wait(sb + FB_X);
            const uint32_t key = lds32(sb + SF_SEL + 4 * r8), x = lds32(sb + SF_XS + r8 * 1168 + 2 * col);
            const int row = key_row(key);
            uint32_t rc;
            for (int it = 0;;) { rc = ld_rlx32(&p.scr->rec[row]); if (((rc >> 14) & 3u) == tag) break; POLL_GUARD(it); }
            const float om = rbf(1.f - bf_lo(rc & 0x3fffu)), rs = rbf(sigmoidf_(key_val(key)));
            __syncwarp();
            mbar_wait(sb + FB_GU);
            for (int it = 0; ld_acq32(&p.scr->zero[8 * (2 * (col >> 4) + ((row >> 6) & 1))]) != tag;) POLL_GUARD(it);
            __syncwarp();
            bar_sync(12, 288);
            float y0 = 0.f, y1 = 0.f;
#pragma unroll
            for (int k = 6; k < 12; k++) {
                const uint32_t ra = sb + SP_RED + 768 * k + (i >> 3) * 64 + r8 * 4;
                y0 += __uint_as_float(lds32(ra)); y1 += __uint_as_float(lds32(ra + 32));
            }
            red_bf2(p.out + row * DM + col, pack_bf16(om * rbf(bf_lo(x) + rbf(rbf(y0) * rs)), om * rbf(bf_hi(x) + rbf(rbf(y1) * rs))));
            return;
        }
    ffn_worker(p, m, sb, f, pure, pure ? warp : warp - 8, t0, tag, tn);
}

__global__ void __cluster_dims__(2, 1, 1) __launch_bounds__(NTHR, 1)
fused_kernel(const Params p, const __grid_constant__ CUtensorMap mU, const __grid_constant__ CUtensorMap mU2, const __grid_constant__ CUtensorMap mR,
             const __grid_constant__ CUtensorMap mG64, const __grid_constant__ CUtensorMap mU64, const __grid_constant__ CUtensorMap mG32,
             const __grid_constant__ CUtensorMap mU32, const __grid_constant__ CUtensorMap mWd) {
    extern __shared__ __align__(1024) uint8_t smem_raw[];
    const uint32_t sb = smem_u32(smem_raw);
    const uint32_t t0 = __shfl_sync(0xffffffffu, clk(), 0);
    const int bx = blockIdx.x;
    const int lane = threadIdx.x & 31, f = bx - FFN0, cb = bx < FFN0 ? bx : bx - NFFN;
    const bool ffn = (unsigned)f < NFFN, pure = (unsigned)f < 48 && !(f & 1);
    const int idx = !ffn ? cb >> 1 : f < 48 ? f >> 1 : f - 24, nch = pure ? 6 : 4, c0 = nch * idx, co = !ffn ? 8 * (bx & 1) : pure ? 12 : 4;
    const int warp = warp_id();
    KParams kp;
    {
        const int w = threadIdx.x >> 5, h = w >= nch, c = c0 + w - nch * h;
        if (w < 2 * nch) kp = kload(p, 4 * (c & ~3) + co + (c & 3), h);
    }
    const int half = warp >= nch, j = warp - nch * half, ch = 4 * ((c0 + j) & ~3) + co + ((c0 + j) & 3);
    uint32_t q[8][4];
    uint4 x[4];
    if (warp < 2 * nch) {
        const uint32_t stage = sb + (!ffn ? SC_STG : pure ? SP_STG : SH_STG), mine = stage + warp * KG_STAGE, other = stage + (half ? j : warp + nch) * KG_STAGE;
        float kv[21], fin;
        cluster_arrive_relaxed();
        kgen(kp, mine, kv, fin, sb);
        if (!(ffn || half)) {
            ksend(kv, fin, mine, false);
            bar_arrive(2 + j, 64);
            mbar_wait(sb + SB_UT);
            conv_windows(sb, warp, q);
            bar_sync(11 + j, 64);
            krecv(kv, fin, other, 0, 17);
            x[3] = kwords8(kv);
        } else {
            ksend(kv, fin, mine, half);
            if (!ffn) bar_arrive(11 + j, 64);
            bar_sync(2 + j, 64);
            if (half) {
                krecv(kv, fin, other, 0, 0); krecv(kv, fin, other, 1, 4); krecv(kv, fin, other, 2, 8); krecv(kv, fin, other, 3, 12);
                kv[16] = kv[16] * fin + __uint_as_float(lds32(other + 2048)) + bf_lo(kp.dskip);
            } else krecv(kv, fin, other, 0, 17);
            if (ffn) { asm volatile("" :: "f"(kv[0]), "f"(kv[4]), "f"(kv[8]), "f"(kv[12]), "f"(kv[16]), "f"(kv[17]) : "memory"); __syncwarp(); if (lane == 0) mbar_arrive(sb + FB_KG); }
            if (half) kpack(kv, x);
            else { x[3] = kwords8(kv); x[0] = x[1] = x[2] = make_uint4(0, 0, 0, 0); }
            if (!ffn) {
                mbar_wait(sb + SB_UT);
                const uint32_t tag = lds32(sb + SC_TAG);
                kpublish(p, ch, tag, x);
                kstore(x, sb + SC_KT + j * KT_BYTES);
                bar_arrive(6 + j, 64);
                conv_windows(sb, warp, q);
                mbar_wait(sb + SB_UT + 8);
                while (clk() - t0 < ((bx & 1) ? KDELAY1 : KDELAY0)) __nanosleep(100);
                kissue<4>(p, ch + 4, x);
                kfetch<4>(p, ch + 4, tag, x);
                kstore(x, sb + SC_KT + warp * KT_BYTES);
                x[3].w = __byte_perm(x[3].w, x[3].z, 0x5410);
            }
        }
    }
    if (!(ffn || warp >= 8)) conv_warp(sb, warp, q, x[3]);
    else if (ffn) { const Maps m = {&mU2, &mR, &mG64, &mU64, &mG32, &mU32, &mWd}; ffn_cta(p, m, sb, f, pure, idx, warp, t0, x, ch); }
    else conv_helper(p, &mU, sb, cb, warp - 8, t0);
}

typedef CUresult (*EncodeFn)(CUtensorMap*, CUtensorMapDataType, cuuint32_t, void*, const cuuint64_t*, const cuuint64_t*, const cuuint32_t*, const cuuint32_t*,
                             CUtensorMapInterleave, CUtensorMapSwizzle, CUtensorMapL2promotion, CUtensorMapFloatOOBfill);

CUtensorMap make_map(EncodeFn fn, const void* base, uint64_t inner, uint64_t outer, uint32_t bi, uint32_t bo, CUtensorMapSwizzle sw,
                     CUtensorMapL2promotion pr = CU_TENSOR_MAP_L2_PROMOTION_NONE) {
    CUtensorMap m;
    cuuint64_t dims[2] = {inner, outer};
    cuuint64_t strides[1] = {inner * 2};
    cuuint32_t box[2] = {bi, bo};
    cuuint32_t es[2] = {1, 1};
    fn(&m, CU_TENSOR_MAP_DATA_TYPE_BFLOAT16, 2, (void*)base, dims, strides, box, es, CU_TENSOR_MAP_INTERLEAVE_NONE, sw, pr, CU_TENSOR_MAP_FLOAT_OOB_FILL_NONE);
    return m;
}

}

extern "C" void kernel_launch(void* const* d_in, const int* in_sizes, int n_in, void* d_out, int out_size) {
    (void)in_sizes; (void)n_in; (void)out_size;
    static EncodeFn fn = nullptr;
    static Scratch* scr = nullptr;
    if (!fn) {
        void* ptr = nullptr; cudaDriverEntryPointQueryResult qr;
        cudaGetDriverEntryPoint("cuTensorMapEncodeTiled", &ptr, cudaEnableDefault, &qr);
        fn = (EncodeFn)ptr;
        cudaGetSymbolAddress((void**)&scr, g_scr);
        cudaFuncSetAttribute(fused_kernel, cudaFuncAttributeMaxDynamicSharedMemorySize, SMEM_BYTES);
    }
    typedef const __nv_bfloat16* bp;
    Params p;
    p.u = (bp)d_in[0]; p.Are = (bp)d_in[1]; p.Aim = (bp)d_in[2]; p.Bre = (bp)d_in[3]; p.Bim = (bp)d_in[4]; p.Cre = (bp)d_in[5]; p.Cim = (bp)d_in[6];
    p.logdt = (bp)d_in[7]; p.Dskip = (bp)d_in[8]; p.wr = (bp)d_in[10]; p.gatew = (bp)d_in[14]; p.wd = (bp)d_in[13];
    p.out = (__nv_bfloat16*)d_out; p.scr = scr;
    CUtensorMap mU, mU2;
    {
        cuuint64_t dims[5] = {DM, 8, 2, L_SEQ / 128, 8};
        cuuint64_t strides[4] = {16 * DM * 2, DM * 2, 128 * DM * 2, 2 * DM * 2};
        cuuint32_t box[5] = {16, 4, 2, 4, 8};
        cuuint32_t es[5] = {1, 1, 1, 1, 1};
        fn(&mU, CU_TENSOR_MAP_DATA_TYPE_BFLOAT16, 5, d_in[0], dims, strides, box, es, CU_TENSOR_MAP_INTERLEAVE_NONE, CU_TENSOR_MAP_SWIZZLE_32B,
           CU_TENSOR_MAP_L2_PROMOTION_NONE, CU_TENSOR_MAP_FLOAT_OOB_FILL_NONE);
        box[3] = NL;
        fn(&mU2, CU_TENSOR_MAP_DATA_TYPE_BFLOAT16, 5, d_in[0], dims, strides, box, es, CU_TENSOR_MAP_INTERLEAVE_NONE, CU_TENSOR_MAP_SWIZZLE_32B,
           CU_TENSOR_MAP_L2_PROMOTION_NONE, CU_TENSOR_MAP_FLOAT_OOB_FILL_NONE);
    }
    CUtensorMap mR, mWd;
    {
        cuuint64_t dims[3] = {64, L_SEQ, 9};
        cuuint64_t strides[2] = {DM * 2, 128};
        cuuint32_t box[3] = {64, 8, 9};
        cuuint32_t es[3] = {1, 1, 1};
        fn(&mR, CU_TENSOR_MAP_DATA_TYPE_BFLOAT16, 3, d_in[0], dims, strides, box, es, CU_TENSOR_MAP_INTERLEAVE_NONE, CU_TENSOR_MAP_SWIZZLE_128B,
           CU_TENSOR_MAP_L2_PROMOTION_NONE, CU_TENSOR_MAP_FLOAT_OOB_FILL_NONE);
        dims[0] = 32; dims[1] = FF; dims[2] = 18; strides[1] = 64; box[0] = box[1] = 32;
        fn(&mWd, CU_TENSOR_MAP_DATA_TYPE_BFLOAT16, 3, d_in[13], dims, strides, box, es, CU_TENSOR_MAP_INTERLEAVE_NONE, CU_TENSOR_MAP_SWIZZLE_64B,
           CU_TENSOR_MAP_L2_PROMOTION_L2_128B, CU_TENSOR_MAP_FLOAT_OOB_FILL_NONE);
    }
    const CUtensorMap mG64 = make_map(fn, d_in[11], FF, DM, 64, 64, CU_TENSOR_MAP_SWIZZLE_128B);
    const CUtensorMap mU64 = make_map(fn, d_in[12], FF, DM, 64, 64, CU_TENSOR_MAP_SWIZZLE_128B);
    const CUtensorMap mG32 = make_map(fn, d_in[11], FF, DM, 32, 64, CU_TENSOR_MAP_SWIZZLE_64B, CU_TENSOR_MAP_L2_PROMOTION_L2_128B);
    const CUtensorMap mU32 = make_map(fn, d_in[12], FF, DM, 32, 64, CU_TENSOR_MAP_SWIZZLE_64B, CU_TENSOR_MAP_L2_PROMOTION_L2_128B);
    fused_kernel<<<NCTA, NTHR, SMEM_BYTES>>>(p, mU, mU2, mR, mG64, mU64, mG32, mU32, mWd);
}
```

```cpp
#include <cuda_runtime.h>
#include <cuda_bf16.h>
#include <cuda_fp16.h>
#include <cuda.h>
#include <stdint.h>

#define RDELAY 1300
#define VDELAY 1100
#define HDELAY 2100
#define WDELAY 1800
#define WPER0 870
#define WPER 730
#define DPER 320
#define PDELAY 5500
#define SDELAY 7300
#define KDELAY0 6300
#define KDELAY1 6900
#define KDELAY2 6000
#define KDELAY3 6000
#define KDELAY4 6900
#define GDELAY 400
#define PACE 20
#define SPLITM 3
#define SPLITJ 2
#define AMODE_U 0
#define AMODE_H 3
#define LOOK 0
#define NOUT 2
#define JBAR 1

namespace {

constexpr int L_SEQ = 2048, DM = 576, NST = 128, FF = 4608;
constexpr int NCTA = 132, NFFN = 60, FFN0 = 8, NTHR = 512;
#define NLOW 5
constexpr int NL = NLOW;

struct Scratch {
    unsigned launch; unsigned pad0[31];
    uint32_t sel[32];
    uint32_t zero[72 * 8];
    uint32_t rec[2 * L_SEQ];
    uint4 kx[DM * 4 * 32];
    uint4 part[24 * 30 * 32];
};
__device__ Scratch g_scr;

struct Params {
    const __nv_bfloat16 *Are, *Aim, *Bre, *Bim, *Cre, *Cim, *logdt, *Dskip, *u, *wr, *gatew, *wd;
    __nv_bfloat16* out;
    Scratch* scr;
    const char* consts;
};

__device__ __forceinline__ uint32_t smem_u32(const void* p) { return (uint32_t)__cvta_generic_to_shared(p); }
__device__ __forceinline__ uint32_t pack_bf16(float lo, float hi) { uint32_t r; asm("cvt.rn.bf16x2.f32 %0, %1, %2;" : "=r"(r) : "f"(hi), "f"(lo)); return r; }
__device__ __forceinline__ uint32_t pack_f16(float lo, float hi) { uint32_t r; asm("cvt.rn.f16x2.f32 %0, %1, %2;" : "=r"(r) : "f"(hi), "f"(lo)); return r; }
__device__ __forceinline__ uint32_t prmt(uint32_t a, uint32_t b, uint32_t c) { uint32_t r; asm("prmt.b32 %0, %1, %2, %3;" : "=r"(r) : "r"(a), "r"(b), "r"(c)); return r; }
__device__ __forceinline__ float bf_lo(uint32_t w) { return __uint_as_float(w << 16); }
__device__ __forceinline__ float bf_hi(uint32_t w) { return __uint_as_float(w & 0xffff0000u); }
__device__ __forceinline__ float rbf(float x) { return bf_lo(pack_bf16(x, 0.f)); }
__device__ __forceinline__ uint32_t hmul2(uint32_t a, uint32_t b) { __nv_bfloat162 r = __hmul2_rn(*(__nv_bfloat162*)&a, *(__nv_bfloat162*)&b); return *(uint32_t*)&r; }
__device__ __forceinline__ uint32_t hfma2(uint32_t a, uint32_t b, uint32_t c) { uint32_t r; asm("fma.rn.bf16x2 %0, %1, %2, %3;" : "=r"(r) : "r"(a), "r"(b), "r"(c)); return r; }
__device__ __forceinline__ uint32_t hsub2(uint32_t a, uint32_t b) { __nv_bfloat162 r = __hsub2_rn(*(__nv_bfloat162*)&a, *(__nv_bfloat162*)&b); return *(uint32_t*)&r; }
__device__ __forceinline__ void mma_bf(float (&c)[4], uint32_t a0, uint32_t a1, uint32_t a2, uint32_t a3, uint32_t b0, uint32_t b1) {
    asm("mma.sync.aligned.m16n8k16.row.col.f32.bf16.bf16.f32 {%0,%1,%2,%3}, {%4,%5,%6,%7}, {%8,%9}, {%0,%1,%2,%3};"
        : "+f"(c[0]), "+f"(c[1]), "+f"(c[2]), "+f"(c[3]) : "r"(a0), "r"(a1), "r"(a2), "r"(a3), "r"(b0), "r"(b1));
}
__device__ __forceinline__ void mma_bf0(float (&c)[4], uint32_t a0, uint32_t a1, uint32_t a2, uint32_t a3, uint32_t b0, uint32_t b1) {
    asm("mma.sync.aligned.m16n8k16.row.col.f32.bf16.bf16.f32 {%0,%1,%2,%3}, {%4,%5,%6,%7}, {%8,%9}, {%10,%10,%10,%10};"
        : "=f"(c[0]), "=f"(c[1]), "=f"(c[2]), "=f"(c[3]) : "r"(a0), "r"(a1), "r"(a2), "r"(a3), "r"(b0), "r"(b1), "f"(0.f));
}
__device__ __forceinline__ void mma_bf8(float (&c)[4], uint32_t a0, uint32_t a1, uint32_t b0) {
    asm("mma.sync.aligned.m16n8k8.row.col.f32.bf16.bf16.f32 {%0,%1,%2,%3}, {%4,%5}, {%6}, {%0,%1,%2,%3};"
        : "+f"(c[0]), "+f"(c[1]), "+f"(c[2]), "+f"(c[3]) : "r"(a0), "r"(a1), "r"(b0));
}
__device__ __forceinline__ void mma_f16(float (&c)[4], uint32_t a0, uint32_t a1, uint32_t a2, uint32_t a3, uint32_t b0, uint32_t b1) {
    asm("mma.sync.aligned.m16n8k16.row.col.f32.f16.f16.f32 {%0,%1,%2,%3}, {%4,%5,%6,%7}, {%8,%9}, {%0,%1,%2,%3};"
        : "+f"(c[0]), "+f"(c[1]), "+f"(c[2]), "+f"(c[3]) : "r"(a0), "r"(a1), "r"(a2), "r"(a3), "r"(b0), "r"(b1));
}
__device__ __forceinline__ uint32_t lds32(uint32_t a) { uint32_t v; asm volatile("ld.shared.u32 %0, [%1];" : "=r"(v) : "r"(a)); return v; }
__device__ __forceinline__ uint32_t lds32v(uint32_t a) { uint32_t v; asm volatile("ld.volatile.shared.u32 %0, [%1];" : "=r"(v) : "r"(a)); return v; }
__device__ __forceinline__ uint2 lds64(uint32_t a) { uint2 v; asm volatile("ld.shared.v2.u32 {%0,%1}, [%2];" : "=r"(v.x), "=r"(v.y) : "r"(a)); return v; }
__device__ __forceinline__ uint4 lds128(uint32_t a) { uint4 v; asm volatile("ld.shared.v4.u32 {%0,%1,%2,%3}, [%4];" : "=r"(v.x), "=r"(v.y), "=r"(v.z), "=r"(v.w) : "r"(a)); return v; }
__device__ __forceinline__ void ldsm4(uint32_t (&r)[4], uint32_t a) {
    asm volatile("ldmatrix.sync.aligned.m8n8.x4.shared.b16 {%0,%1,%2,%3}, [%4];" : "=r"(r[0]), "=r"(r[1]), "=r"(r[2]), "=r"(r[3]) : "r"(a));
}
__device__ __forceinline__ void ldsm2(uint32_t (&r)[4], uint32_t a) {
    asm volatile("ldmatrix.sync.aligned.m8n8.x2.shared.b16 {%0,%1}, [%2];" : "=r"(r[0]), "=r"(r[1]) : "r"(a));
}
__device__ __forceinline__ void ldsm4t(uint32_t (&r)[4], uint32_t a) {
    asm volatile("ldmatrix.sync.aligned.m8n8.x4.trans.shared.b16 {%0,%1,%2,%3}, [%4];" : "=r"(r[0]), "=r"(r[1]), "=r"(r[2]), "=r"(r[3]) : "r"(a));
}
__device__ __forceinline__ void sts32(uint32_t a, uint32_t v) { asm volatile("st.shared.u32 [%0], %1;" :: "r"(a), "r"(v) : "memory"); }
__device__ __forceinline__ void sts64(uint32_t a, uint32_t x, uint32_t y) { asm volatile("st.shared.v2.u32 [%0], {%1,%2};" :: "r"(a), "r"(x), "r"(y) : "memory"); }
__device__ __forceinline__ void sts128(uint32_t a, uint32_t x, uint32_t y, uint32_t z, uint32_t w) {
    asm volatile("st.shared.v4.u32 [%0], {%1,%2,%3,%4};" :: "r"(a), "r"(x), "r"(y), "r"(z), "r"(w) : "memory");
}
__device__ __forceinline__ void stsm2(uint32_t a, uint32_t x, uint32_t y) {
    asm volatile("stmatrix.sync.aligned.m8n8.x2.shared.b16 [%0], {%1,%2};" :: "r"(a), "r"(x), "r"(y) : "memory");
}
__device__ __forceinline__ void stsm4t(uint32_t a, uint32_t r0, uint32_t r1, uint32_t r2, uint32_t r3) {
    asm volatile("stmatrix.sync.aligned.m8n8.x4.trans.shared.b16 [%0], {%1,%2,%3,%4};" :: "r"(a), "r"(r0), "r"(r1), "r"(r2), "r"(r3) : "memory");
}
__device__ __forceinline__ void st_async32(uint32_t a, uint32_t x, uint32_t bar) {
    asm volatile("st.async.weak.shared::cluster.mbarrier::complete_tx::bytes.b32 [%0], %1, [%2];" :: "r"(a), "r"(x), "r"(bar) : "memory");
}
__device__ __forceinline__ void st_async128(uint32_t a, uint32_t x, uint32_t y, uint32_t z, uint32_t w, uint32_t bar) {
    asm volatile("st.async.weak.shared::cluster.mbarrier::complete_tx::bytes.v4.b32 [%0], {%1,%2,%3,%4}, [%5];" :: "r"(a), "r"(x), "r"(y), "r"(z), "r"(w), "r"(bar) : "memory");
}
__device__ __forceinline__ void mbar_init(uint32_t b, uint32_t cnt) { asm volatile("mbarrier.init.shared::cta.b64 [%0], %1;" :: "r"(b), "r"(cnt) : "memory"); }
__device__ __forceinline__ void mbar_fence_init() { asm volatile("fence.mbarrier_init.release.cluster;" ::: "memory"); }
__device__ __forceinline__ void mbar_expect(uint32_t b, uint32_t bytes) { asm volatile("mbarrier.arrive.expect_tx.shared::cta.b64 _, [%0], %1;" :: "r"(b), "r"(bytes) : "memory"); }
__device__ __forceinline__ void mbar_arrive(uint32_t b) { asm volatile("mbarrier.arrive.shared::cta.b64 _, [%0];" :: "r"(b) : "memory"); }
__device__ __forceinline__ void mbar_arrive_peer(uint32_t b) { asm volatile("mbarrier.arrive.relaxed.cluster.shared::cluster.b64 _, [%0];" :: "r"(b) : "memory"); }
__device__ __forceinline__ void mbar_wait(uint32_t b) {
    asm volatile("{ .reg .pred p;\nW: mbarrier.try_wait.parity.shared::cta.b64 p, [%0], 0; @!p bra W; }" :: "r"(b) : "memory");
}
__device__ __forceinline__ void tma2d(uint32_t dst, const CUtensorMap* m, int c0, int c1, uint32_t bar) {
    asm volatile("cp.async.bulk.tensor.2d.shared::cluster.global.mbarrier::complete_tx::bytes [%0], [%1, {%3, %4}], [%2];"
                 :: "r"(dst), "l"(m), "r"(bar), "r"(c0), "r"(c1) : "memory");
}
__device__ __forceinline__ void tma3d(uint32_t dst, const CUtensorMap* m, int c0, int c1, int c2, uint32_t bar) {
    asm volatile("cp.async.bulk.tensor.3d.shared::cluster.global.mbarrier::complete_tx::bytes [%0], [%1, {%3, %4, %5}], [%2];"
                 :: "r"(dst), "l"(m), "r"(bar), "r"(c0), "r"(c1), "r"(c2) : "memory");
}
__device__ __forceinline__ void tma5d(uint32_t dst, const CUtensorMap* m, int c0, int c1, int c2, int c3, int c4, uint32_t bar) {
    asm volatile("cp.async.bulk.tensor.5d.shared::cluster.global.mbarrier::complete_tx::bytes [%0], [%1, {%3, %4, %5, %6, %7}], [%2];"
                 :: "r"(dst), "l"(m), "r"(bar), "r"(c0), "r"(c1), "r"(c2), "r"(c3), "r"(c4) : "memory");
}
__device__ __forceinline__ void bulk_load(uint32_t dst, const void* src, uint32_t bytes, uint32_t bar) {
    asm volatile("cp.async.bulk.shared::cluster.global.mbarrier::complete_tx::bytes [%0], [%1], %2, [%3];" :: "r"(dst), "l"(src), "r"(bytes), "r"(bar) : "memory");
}
__device__ __forceinline__ bool elect() { uint32_t d; asm volatile("{ .reg .pred p; elect.sync _|p, 0xffffffff; selp.u32 %0, 1, 0, p; }" : "=r"(d)); return d; }
__device__ __forceinline__ void prefetch_l2(const void* src, uint32_t bytes) { asm volatile("cp.async.bulk.prefetch.L2.global [%0], %1;" :: "l"(src), "r"(bytes) : "memory"); }
__device__ __forceinline__ uint32_t mapa(uint32_t a, uint32_t rank) { uint32_t r; asm("mapa.shared::cluster.u32 %0, %1, %2;" : "=r"(r) : "r"(a), "r"(rank)); return r; }
__device__ __forceinline__ void prefetch_map(const CUtensorMap* m) { asm volatile("prefetch.tensormap [%0];" :: "l"(m) : "memory"); }
__device__ __forceinline__ void bar_sync(int id, int n) { asm volatile("bar.sync %0, %1;" :: "r"(id), "r"(n) : "memory"); }
__device__ __forceinline__ void bar_arrive(int id, int n) { asm volatile("bar.arrive %0, %1;" :: "r"(id), "r"(n) : "memory"); }
__device__ __forceinline__ void cluster_arrive_relaxed() { asm volatile("barrier.cluster.arrive.relaxed.aligned;" ::: "memory"); }
__device__ __forceinline__ void cluster_wait() { asm volatile("barrier.cluster.wait.aligned;" ::: "memory"); }
__device__ __forceinline__ uint32_t ld_rlx32(const void* p) { uint32_t v; asm volatile("ld.relaxed.gpu.global.u32 %0, [%1];" : "=r"(v) : "l"(p) : "memory"); return v; }
__device__ __forceinline__ uint4 ld_rlx128(const void* p) {
    uint4 v; asm volatile("ld.relaxed.gpu.global.v4.u32 {%0,%1,%2,%3}, [%4];" : "=r"(v.x), "=r"(v.y), "=r"(v.z), "=r"(v.w) : "l"(p) : "memory"); return v;
}
__device__ __forceinline__ uint32_t ld_acq32(const void* p) { uint32_t v; asm volatile("ld.acquire.gpu.global.u32 %0, [%1];" : "=r"(v) : "l"(p) : "memory"); return v; }
__device__ __forceinline__ void red_bf2(void* p, uint32_t v) { asm volatile("red.relaxed.gpu.global.add.noftz.bf16x2 [%0], %1;" :: "l"(p), "r"(v) : "memory"); }
__device__ __forceinline__ uint32_t take_ticket(unsigned* p) { uint32_t v; asm volatile("atom.relaxed.gpu.global.add.u32 %0, [%1], 1;" : "=r"(v) : "l"(p) : "memory"); return v; }
__device__ __forceinline__ void st_rlx32(void* p, uint32_t v) { asm volatile("st.relaxed.gpu.global.u32 [%0], %1;" :: "l"(p), "r"(v) : "memory"); }
__device__ __forceinline__ void st_pkt(void* p, uint32_t x, uint32_t y, uint32_t z, uint32_t w) {
    asm volatile("{ .reg .b64 lo, hi; .reg .b128 v; mov.b64 lo, {%1, %2}; mov.b64 hi, {%3, %4}; mov.b128 v, {lo, hi}; st.relaxed.gpu.global.b128 [%0], v; }"
                 :: "l"(p), "r"(x), "r"(y), "r"(z), "r"(w) : "memory");
}
__device__ __forceinline__ uint4 ld_pkt(const void* p) {
    uint4 r;
    asm volatile("{ .reg .b64 lo, hi; .reg .b128 v; ld.relaxed.gpu.global.b128 v, [%4]; mov.b128 {lo, hi}, v; mov.b64 {%0, %1}, lo; mov.b64 {%2, %3}, hi; }"
                 : "=r"(r.x), "=r"(r.y), "=r"(r.z), "=r"(r.w) : "l"(p) : "memory");
    return r;
}
__device__ __forceinline__ uint32_t tag_of(uint32_t ticket) { return ticket / NCTA % 3u + 1u; }
__device__ __forceinline__ uint32_t ldg32(const void* p) { uint32_t v; asm volatile("ld.global.nc.u32 %0, [%1];" : "=r"(v) : "l"(p)); return v; }
__device__ __forceinline__ uint32_t ldg16(const void* p) { uint32_t v; asm volatile("ld.global.nc.u16 %0, [%1];" : "=r"(v) : "l"(p)); return v; }
__device__ __forceinline__ int warp_id() { return __shfl_sync(0xffffffffu, threadIdx.x >> 5, 0); }
__device__ __forceinline__ int lane_id() {
    const int l = __shfl_sync(0xffffffffu, threadIdx.x & 31, threadIdx.x);
    __builtin_assume(l >= 0 && l < 32);
    return l;
}
__device__ __forceinline__ uint32_t clk() { uint32_t t; asm volatile("mov.u32 %0, %clock;" : "=r"(t) :: "memory"); return t; }
__device__ __forceinline__ void spin_until(uint32_t t0, uint32_t d) { while (clk() - t0 < d) {} }
template <int NS>
__device__ __forceinline__ void sleep_until(uint32_t t) {
    asm volatile("{ .reg .pred p; .reg .s32 c;\nW: mov.u32 c, %clock; sub.s32 c, c, %0; setp.lt.s32 p, c, 0; @p nanosleep.u32 %1; @p bra W; }" :: "r"(t), "n"(NS) : "memory");
}
__device__ __forceinline__ float sigmoidf_(float x) { return __fdividef(1.0f, 1.0f + __expf(-x)); }
__device__ __forceinline__ int key_row(uint32_t key) { return 2047 - (int)(key & 2047u); }
__device__ __forceinline__ uint32_t key_thr(uint32_t key) { return __byte_perm(key & 2047u, key << 3, 0x7610); }
__device__ __forceinline__ float key_val(uint32_t key) {
    const uint32_t o = (key << 3) & 0xffff0000u; return __uint_as_float((o & 0x80000000u) ? (o & 0x7fffffffu) : (~o & 0xffff0000u));
}
#define RARE(x) __builtin_expect(!!(x), 0)
#define POLL_GUARD(it) (void)(it)

constexpr int UT_PL = 2240, UT_STRIDE = 4544;
constexpr int KT_P = 0, KT_P4 = 544 * 4, KT_P8 = KT_P4 + 172 * 4, KT_BYTES = KT_P8 + 140 * 4;
constexpr int KG_ROW = 272, KG_STAGE = 33 * KG_ROW;
constexpr int OUT_HALF = 2368, OUT_STAGE = 2 * OUT_HALF;
constexpr int SC_UTILE = 0;
constexpr int SC_UT = 32768;
constexpr int SC_STG = SC_UT + 8 * UT_STRIDE;
constexpr int SC_KT = SC_STG + 8 * KG_STAGE;
constexpr int SC_OUT = SC_KT + 8 * KT_BYTES;
constexpr int SC_CT = SC_OUT + 8 * OUT_STAGE;
constexpr int SC_BAR = SC_CT + 4096;
constexpr int SB_UT = SC_BAR + 32, SB_OUT = SC_BAR + 64, SC_KEY = SC_BAR + 128, SC_TAG = SC_BAR + 160;
constexpr int SC_END = SC_BAR + 256;
static_assert(SC_STG % 128 == 0 && SC_OUT % 128 == 0 && SC_KT % 16 == 0, "align");
constexpr int PIECE_P = 24576, PIECE_H = 16384, DPIECE = 18432;
constexpr int SF_LIST = 9 * PIECE_P, SF_WR = SF_LIST + 4096;
constexpr int SF_XS = SF_LIST + 384;
constexpr int SF_BAR = SF_XS + 9344;
constexpr int FB_W = SF_BAR, FB_D = FB_W + 72, FB_GU = FB_D + 40, FB_FREE = FB_GU + 8, FB_SEL = FB_FREE + 16, FB_KG = FB_SEL + 8, FB_TK = FB_KG + 8, FB_UT = FB_TK + 8,
              FB_X = FB_UT + 8, FB_WR = FB_X + 8, FB_PEER = FB_WR + 8, FB_R = FB_PEER + 16, FB_RAW = FB_R + 48;
constexpr int SF_MAX = FB_RAW + 8, SF_CNT = SF_MAX + 64, SF_TK = SF_CNT + 4, SF_CLK = SF_CNT + 8, SF_TN = SF_CNT + 16, SF_SEL = SF_CNT + 32;
constexpr int SF_END = SF_SEL + 32;
constexpr int SP_R = 83 * 1024, SP_STG = SF_LIST - 12 * KG_STAGE, SP_H = DPIECE, SP_RED = 5 * PIECE_P;
constexpr int UH_PL = 128 + 128 * NL + 64, UH_STRIDE = 2 * UH_PL - 64, UH_HI = 8 * UH_STRIDE + 32, KH_BYTES = KT_P4 + 176 * 4, OH_STRIDE = 512 * ((NL + 1) / 2) + 64;
constexpr int SH_UT = 9 * PIECE_H, SH_R = SH_UT, SH_R5 = 4 * PIECE_H, SH_STG = SH_UT - 8 * KG_STAGE, SH_H = SH_UT + 16 * UH_STRIDE + 128, SH_OUT = SH_H + 2560;
constexpr int SH_CT = SH_R + 5 * 9216, SH_RAW = SF_LIST - NL * 4096, SH_KT = SF_LIST - 8 * KH_BYTES;
constexpr int SM_TIM = SF_END;
constexpr int SMEM_BYTES = SF_END + 272;
static_assert(SP_R + 3 * 9216 <= SP_STG && SP_R >= 3 * PIECE_P && SP_STG >= 4 * PIECE_P && SH_R5 + 9216 <= SH_STG && SH_OUT + 8 * OH_STRIDE <= SH_CT && (SH_KT - SH_OUT) % 64 == 0 && KH_BYTES % 128 == 64 && SH_CT + 3584 <= SH_RAW &&
              SH_CT + 3584 <= SH_KT && SF_MAX % 16 == 0 && SMEM_BYTES <= 232448 && SC_END <= SF_END, "smem");

struct cplx { float re, im; };
struct h2c { uint32_t re, im; };
__device__ __forceinline__ cplx csq(cplx a) {
    cplx r; r.re = a.re * a.re - a.im * a.im;
    asm("{ .reg .f32 t; mul.f32 t, %1, %2; mul.f32 %0, t, 0f40000000; }" : "=f"(r.im) : "f"(a.re), "f"(a.im));
    return r;
}
__device__ __forceinline__ float ex2(float x) { float m; asm("ex2.approx.ftz.f32 %0, %1;" : "=f"(m) : "f"(x)); return m; }
__device__ __forceinline__ cplx cexp2(float x, float y) {
    const float m = ex2(x);
    cplx o; o.re = m * __cosf(y); o.im = m * __sinf(y); return o;
}
__device__ __forceinline__ h2c hpack(cplx a, cplx b) { h2c r; r.re = pack_f16(a.re, b.re); r.im = pack_f16(a.im, b.im); return r; }
__device__ __forceinline__ h2c hmulc(h2c a, h2c m) {
    h2c r;
    asm("{ .reg .b32 s, t; mul.f16x2 s, %3, %5; mul.f16x2 t, %3, %4; neg.f16x2 s, s; fma.rn.f16x2 %0, %2, %4, s; fma.rn.f16x2 %1, %2, %5, t; }"
        : "=&r"(r.re), "=r"(r.im) : "r"(a.re), "r"(a.im), "r"(m.re), "r"(m.im));
    return r;
}
__device__ __forceinline__ h2c hmulj(h2c a, h2c m) {
    h2c r;
    asm("{ .reg .b32 s, t; mul.f16x2 s, %3, %5; mul.f16x2 t, %2, %5; neg.f16x2 t, t; fma.rn.f16x2 %0, %2, %4, s; fma.rn.f16x2 %1, %3, %4, t; }"
        : "=&r"(r.re), "=r"(r.im) : "r"(a.re), "r"(a.im), "r"(m.re), "r"(m.im));
    return r;
}

struct KParams { uint32_t v[6], logdt, dskip; };
__device__ __forceinline__ KParams kload(const Params& p, int ch, int half) {
    KParams k;
    const int o = ch * NST + 64 * half + 2 * (threadIdx.x & 31);
    const __nv_bfloat16* a[8] = {p.Are + o, p.Aim + o, p.Bre + o, p.Bim + o, p.Cre + o, p.Cim + o, p.logdt + ch, p.Dskip + ch};
#pragma unroll
    for (int i = 0; i < 6; i++) k.v[i] = ldg32(a[i]);
    k.logdt = ldg16(a[6]);
    k.dskip = ldg16(a[7]);
    return k;
}

__device__ __forceinline__ void kgen(int lane, const KParams& k, uint32_t stage, float (&kv)[21], float& fin, uint32_t sb) {
    const int mi = lane >> 3, r8 = lane & 7;
    const uint32_t (&v)[6] = k.v;
    const uint32_t w2 = stage + (lane & 15) * 16, w1 = stage + lane * 4;
    auto put = [&](int row, h2c x) { stsm2(w2 + row * KG_ROW, x.re, x.im); };
    auto keep = [&](int row, h2c x) { sts32(w1 + row * KG_ROW, x.re); sts32(w1 + row * KG_ROW + 128, x.im); };
    sts32(w1, 0x3c003c00u); sts32(w1 + 128, 0u);
    const float dt = rbf(ex2(bf_lo(k.logdt) * 1.4426950408889634f));
    const float dl = dt * 1.4426950408889634f;
    const float xa = bf_lo(v[0]) * dl, xb = bf_hi(v[0]) * dl, ya = bf_lo(v[1]) * dt, yb = bf_hi(v[1]) * dt;
    cplx a = cexp2(xa, ya), b = cexp2(xb, yb), c = cexp2(64.f * xa, 64.f * ya), d = cexp2(64.f * xb, 64.f * yb);
    cplx Wa, Wb;
    Wa.re = bf_lo(v[4]) * bf_lo(v[2]) - bf_lo(v[5]) * bf_lo(v[3]); Wa.im = bf_lo(v[4]) * bf_lo(v[3]) + bf_lo(v[5]) * bf_lo(v[2]);
    Wb.re = bf_hi(v[4]) * bf_hi(v[2]) - bf_hi(v[5]) * bf_hi(v[3]); Wb.im = bf_hi(v[4]) * bf_hi(v[3]) + bf_hi(v[5]) * bf_hi(v[2]);
    const float mx = fmaxf(fmaxf(fabsf(Wa.re), fabsf(Wa.im)), fmaxf(fabsf(Wb.re), fabsf(Wb.im)));
    const uint32_t ex = max(__reduce_max_sync(0xffffffffu, __float_as_uint(mx)) >> 23, 10u);
    const float sc = __uint_as_float((263u - ex) << 23);
    fin = dt * __uint_as_float((ex - 9u) << 23);
    Wa.re *= sc; Wa.im *= sc; Wb.re *= sc; Wb.im *= sc;
    kv[16] = (float)__reduce_add_sync(0xffffffffu, __float2int_rn((Wa.re + Wb.re) * 32768.f)) * (1.f / 32768.f);
    h2c c1;
    {
        cplx p, q;
        p.re = Wa.re * a.re - Wa.im * a.im; p.im = -(Wa.re * a.im) - Wa.im * a.re; q.re = Wb.re * b.re - Wb.im * b.im; q.im = -(Wb.re * b.im) - Wb.im * b.re;
        c1 = hpack(p, q);
    }
    const h2c z1 = hpack(a, b); a = csq(a); b = csq(b);
    const h2c z64 = hpack(c, d); c = csq(c); d = csq(d);
    const h2c z2 = hpack(a, b); a = csq(a); b = csq(b);
    const h2c z128 = hpack(c, d); c = csq(c); d = csq(d);
    const h2c z4 = hpack(a, b); a = csq(a); b = csq(b);
    const h2c z256 = hpack(c, d); c = csq(c); d = csq(d);
    const h2c z8 = hpack(a, b); a = csq(a); b = csq(b);
    const h2c z512 = hpack(c, d);
    const h2c z16 = hpack(a, b); a = csq(a); b = csq(b);
    const h2c z32 = hpack(a, b);
    keep(32, z64);
    const h2c c2 = hmulj(c1, z1), c3 = hmulj(c1, z2), c4 = hmulj(c2, z2), c6 = hmulj(c2, z4), c8 = hmulj(c4, z4);
    keep(8, c1); keep(9, c2); keep(10, c3); keep(11, c4); put(12, hmulj(c1, z4)); keep(13, c6); put(14, hmulj(c3, z4)); keep(15, c8);
    const h2c e260 = hmulj(c4, z256), e264 = hmulj(c8, z256), e776 = hmulj(e264, z512), e840 = hmulj(e776, z64);
    put(16, hmulj(c2, z256)); put(17, hmulj(c4, z512)); keep(18, e260); put(19, hmulj(c8, z512)); put(20, hmulj(c6, z256)); put(21, hmulj(e260, z512)); keep(22, e264); keep(23, e776);
    const h2c z24 = hmulc(z8, z16);
    keep(1, z8); keep(2, z16); keep(3, z24); keep(4, z32); put(5, hmulc(z8, z32)); put(6, hmulc(z16, z32)); put(7, hmulc(z24, z32));
    const h2c d0 = hmulj(e840, z128), d1 = hmulj(e840, z256), d3 = hmulj(e840, z512), d2 = hmulj(d0, z256);
    keep(24, d0); keep(25, d1); keep(27, d3); keep(26, d2); put(28, hmulj(d0, z512)); put(29, hmulj(d1, z512)); put(31, hmulj(d3, z512)); put(30, hmulj(d2, z512));
    __syncwarp();
    cluster_wait();
    const uint32_t ra = stage + ((mi & 1) ? 32 : r8) * KG_ROW + (mi >> 1) * 128, rb = stage + (8 + r8) * KG_ROW + (mi & 1) * 128 + (mi >> 1) * 16;
    float acc[5][4];
#pragma unroll
    for (int i = 0; i < 5; i++) acc[i][0] = acc[i][1] = acc[i][2] = acc[i][3] = 0.f;
#pragma unroll
    for (int s = 0; s < 4; s++) {
        uint32_t A[2][4], B[3][4];
        ldsm4(A[0], ra + 32 * s); ldsm4(A[1], ra + 32 * s + 16);
        ldsm4(B[0], rb + 32 * s); ldsm4(B[1], rb + 32 * s + 8 * KG_ROW); ldsm4(B[2], rb + 32 * s + 16 * KG_ROW);
#pragma unroll
        for (int e = 0; e < 2; e++) {
            const h2c p0 = {A[e][0], A[e][2]}, m = {A[e][1], A[e][3]};
            const h2c p1 = hmulc(p0, m), p2 = hmulc(p1, m), p3 = hmulc(p2, m);
            mma_f16(acc[1], p1.re, p2.re, p1.im, p2.im, B[0][2 * e], B[0][2 * e + 1]);
            mma_f16(acc[3], p1.re, p2.re, p1.im, p2.im, B[1][2 * e], B[1][2 * e + 1]);
            mma_f16(acc[4], p1.re, p2.re, p1.im, p2.im, B[2][2 * e], B[2][2 * e + 1]);
            mma_f16(acc[0], p0.re, p3.re, p0.im, p3.im, B[0][2 * e], B[0][2 * e + 1]);
            mma_f16(acc[2], p0.re, p3.re, p0.im, p3.im, B[1][2 * e], B[1][2 * e + 1]);
        }
    }
#pragma unroll
    for (int q = 0; q < 4; q++) {
        const int i = (q == 1 || q == 2), h = 2 * (q >> 1);
        kv[2 * q] = acc[i][h]; kv[2 * q + 1] = acc[i][h + 1]; kv[8 + q] = acc[2 + i][h]; kv[12 + q] = acc[2 + i][h + 1]; kv[17 + q] = acc[4][2 * (q & 1) + (q >> 1)];
    }
}
__device__ __forceinline__ void ksend(int lane, const float (&kv)[21], float fin, uint32_t mine, bool second) {
    const uint32_t lo = lane * 16;
    auto send = [&](int i, int k) { sts128(mine + lo + 512 * i, __float_as_uint(kv[k] * fin), __float_as_uint(kv[k + 1] * fin), __float_as_uint(kv[k + 2] * fin), __float_as_uint(kv[k + 3] * fin)); };
    __syncwarp();
    if (second) send(0, 17);
    else { send(0, 0); send(1, 4); send(2, 8); send(3, 12); sts32(mine + 2048, __float_as_uint(kv[16] * fin)); }
}
__device__ __forceinline__ void krecv(int lane, float (&kv)[21], float fin, uint32_t other, int i, int k) {
    const uint4 x = lds128(other + lane * 16 + 512 * i);
    kv[k] = kv[k] * fin + __uint_as_float(x.x); kv[k + 1] = kv[k + 1] * fin + __uint_as_float(x.y); kv[k + 2] = kv[k + 2] * fin + __uint_as_float(x.z); kv[k + 3] = kv[k + 3] * fin + __uint_as_float(x.w);
}

__device__ __forceinline__ void kpack(int lane, const float (&kv)[21], uint4 (&x)[4]) {
    const uint32_t w512 = pack_bf16(__shfl_sync(0xffffffffu, kv[11], 31), 0.f);
    const float up = __shfl_up_sync(0xffffffffu, kv[15], 2), k512 = bf_lo(w512);
    x[0] = make_uint4(pack_bf16(kv[1], kv[3]), pack_bf16(kv[5], kv[7]), pack_bf16(kv[8], kv[9]), w512);
    x[1] = make_uint4(pack_bf16(kv[10], lane < 30 ? kv[11] : lane == 31 ? 0.f : kv[11] - k512), pack_bf16(kv[0], kv[2]), pack_bf16(kv[4], kv[6]), 0);
    x[2] = make_uint4(pack_bf16(kv[12], kv[13]), pack_bf16(kv[14], kv[15]), pack_bf16((lane & 2) ? up : lane == 29 ? k512 : 0.f, kv[16]), 0);
}
__device__ __forceinline__ void kstore(int lane, const uint4 (&x)[4], uint32_t kt, uint32_t ct) {
    const uint4 c = lds128(ct + lane * 16 + 2560), d = lds128(ct + lane * 16 + 3072);
    const uint32_t h[4] = {x[0].x, x[0].y, x[0].z, x[1].x}, l[2] = {x[1].y, x[1].z};
    uint32_t carry = x[2].z;
    if (lane == 0) sts32(kt + KT_P + 15 * 4, carry >> 16);
#pragma unroll
    for (int i = 0; i < 4; i++) {
        const uint32_t sh = __shfl_sync(0xffffffffu, h[i], lane + 31), pv = prmt(sh, carry, d.x);
        carry = sh;
#pragma unroll
        for (int e = 0; e < 2; e++) {
            const uint32_t a = kt + KT_P + (128 * i + 64 * e + 16) * 4 + lane * 8;
            if (i < 2) sts64(a, __byte_perm(l[i], pv, 0x5410 + 0x2222 * e), __byte_perm(h[i], l[i], 0x5410 + 0x2222 * e));
            else sts64(a, prmt(h[i], pv, e ? c.z : c.x), prmt(h[i], pv, e ? c.w : c.y));
        }
    }
    const uint32_t a4 = kt + d.y;
    sts32(a4, __byte_perm(x[2].x, x[2].z, 0x5410)); sts32(a4 + 64, __byte_perm(x[2].x, 0, 0x1032));
    sts32(a4 + 128, __byte_perm(x[2].y, x[2].x, 0x7610)); sts32(a4 + 192, __byte_perm(x[2].y, 0, 0x1032));
    sts32(kt + d.z, prmt(x[2].y, x[0].w, d.w));
}
__device__ __forceinline__ uint4 kwords8(int lane, const float (&kv)[21]) {
    const float up = __shfl_up_sync(0xffffffffu, kv[20], 1);
    return make_uint4(pack_bf16(kv[17], (lane & 3) ? up : 0.f), pack_bf16(kv[18], kv[17]), pack_bf16(kv[19], kv[18]), pack_bf16(kv[20], kv[19]));
}

constexpr uint32_t band(int e, int c, int h) { return (((unsigned)(e - c + h) <= 2u * h) ? 0x3f80u : 0u) | (((unsigned)(e + 1 - c + h) <= 2u * h) ? 0x3f800000u : 0u); }

struct alignas(128) Consts { uint32_t a[7][32][4]; };
constexpr Consts conv_consts(int pl) {
    Consts c = {};
    for (int lane = 0; lane < 32; lane++) {
        const int g = lane >> 2, t = lane & 3, mi = lane >> 3, r8 = lane & 7, d0 = g - 2 * t, pg = (g >> 1) + 4 * (g & 1);
        const uint32_t sa = (lane & 1) ? 0x5410 : 0x5454, sb = (lane & 1) ? 0x1010 : 0x5410, a4 = KT_P4 + (13 + 2 * g + (t & 1) + 64 * (t >> 1)) * 4;
        const uint32_t v[28] = {
            band(4 * t, 4 + g, 4), band(4 * t, 4 + g, 3), band(4 * t + 2, 4 + g, 4), band(4 * t + 2, 4 + g, 3),
            (uint32_t)(pg * 16 + (t == 0 ? pl - 8 : t == 3 ? pl : 8 * (t - 1))), (uint32_t)(pg * 16 + (t == 0 ? -8 : t == 3 ? 0 : pl - 16 + 8 * (t - 1))),
            (uint32_t)((mi & 1) * pl + (mi >> 1) * 128 + r8 * 16), (uint32_t)(KT_P + (15 + d0) * 4),
            (((unsigned)(d0 - 3) < 2u) ? 0xffffu : 0u) | (((unsigned)(d0 - 4) < 2u) ? 0xffff0000u : 0u),
            (((unsigned)(d0 + 5) < 2u) ? 0xffffu : 0u) | (((unsigned)(d0 + 4) < 2u) ? 0xffff0000u : 0u), (uint32_t)(KT_P4 + (3 + g - t) * 16), (uint32_t)(pl - 16 + lane * 16),
            band(2 * t, 6 + g, 2), band(2 * t, 2 + g, 1), band(2 * t + 8, 6 + g, 2), band(2 * t + 8, 2 + g, 1),
            (uint32_t)(pg * 16 + (t == 3 ? pl : 4 + 4 * t)), (uint32_t)(pg * 16 + (t == 3 ? 16 : pl + 4 + 4 * t)), 0, 0,
            sa, sb, sa + 0x2222, sb + 0x2222, lane ? 0x3210u : 0x1076u, a4, t >= 2 ? a4 + 256 : KT_P4 + 12 * 4, t >= 2 ? 0x3277u : 0x7754u};
        for (int i = 0; i < 28; i++) c.a[i >> 2][lane][i & 3] = v[i];
    }
    return c;
}
__device__ const Consts g_consts[2] = {conv_consts(UT_PL), conv_consts(UH_PL)};

__device__ __forceinline__ void conv_windows(int lane, uint32_t sb, int warp, uint32_t (&q)[8][4]) {
    const uint32_t ut = sb + SC_UT + warp * UT_STRIDE + 128, ct = sb + SC_CT + lane * 16;
    const uint2 c1 = lds64(ct + 512);
    const uint4 c0 = lds128(ct);
    const uint32_t w0 = c0.x, w1 = c0.y, w2 = c0.z, w3 = c0.w, a0 = ut + c1.x, a1 = ut + c1.y;
#pragma unroll
    for (int j = 0; j < 8; j++) {
        const uint2 x = lds64(a0 + 128 * j - 16), y = lds64(a1 + 128 * j), z = lds64(a0 + 128 * j);
        float X[4], Y[4], Z[4];
        mma_bf0(X, w0, w1, w2, w3, x.x, x.y); mma_bf0(Y, w0, w1, w2, w3, y.x, y.y); mma_bf0(Z, w0, w1, w2, w3, z.x, z.y);
        q[j][0] = pack_bf16(Y[2], Y[3]); q[j][1] = pack_bf16(Z[2], Z[3]); q[j][2] = pack_bf16(X[0], X[1]); q[j][3] = pack_bf16(Y[0], Y[1]);
    }
}
template <int N>
__device__ __forceinline__ void kissue(int lane, const Params& p, int ch, uint4 (&x)[4]) {
    const uint4* src = p.scr->kx + ch * 128 + lane;
#pragma unroll
    for (int i = 0; i < N; i++) x[i] = ld_pkt(src + 32 * i);
}
template <int N>
__device__ __forceinline__ void kfetch(int lane, const Params& p, int ch, uint32_t tag, uint4 (&x)[4]) {
    tag <<= 16;
    for (int it = 0; !__all_sync(0xffffffffu, ((x[0].w ^ tag) | (x[1].w ^ tag) | (x[2].w ^ tag) | (x[N - 1].w ^ tag)) < 0x10000u);) {
        kissue<N>(lane, p, ch, x);
        POLL_GUARD(it);
    }
}
__device__ __forceinline__ void kpublish(int lane, const Params& p, int ch, uint32_t tag, uint4 (&x)[4]) {
    uint4* const dst = p.scr->kx + ch * 128 + lane;
#pragma unroll
    for (int i = 0; i < 3; i++) { x[i].w |= tag << 16; st_pkt(dst + 32 * i, x[i].x, x[i].y, x[i].z, x[i].w); }
}

template <int LO, int HI>
__device__ __forceinline__ void conv_core(float (&acc)[16][4], uint32_t sb, int warp, uint32_t kt, uint32_t ut, uint32_t ct, uint32_t out) {
    const uint32_t oz = blockIdx.y;
    const uint2 c1 = lds64(ct + 520);
    uint4 c2;
    {
        uint32_t a[4][4], b[8][4];
        uint32_t k1 = kt + c1.y, u1 = ut + c1.x;
        constexpr int AM = LO ? AMODE_U : AMODE_H;
        auto lda = [&](int j1, bool first) {
            a[j1][2] = (AM & 1) && !first ? a[j1][1] + oz : lds32v(k1 + 512 * j1 - 32);
            a[j1][0] = lds32(k1 + 512 * j1); a[j1][1] = lds32(k1 + 512 * j1 + 32);
            a[j1][3] = (AM & 2) ? a[j1][0] + oz : lds32v(k1 + 512 * j1);
        };
        auto ldb = [&](int m2) { if (2 * m2 + 1 < HI) ldsm4(b[m2], u1 + 256 * m2); else ldsm2(b[m2], u1 + 256 * m2); };
        lda(0, true);
#pragma unroll
        for (int m2 = LO / 2; m2 < (HI + 1) / 2; m2++) ldb(m2);
#pragma unroll
        for (int i = 0; i < (LO ? 8 : 16); i++) acc[i][0] = acc[i][1] = acc[i][2] = acc[i][3] = 0.f;
        auto pass = [&](bool last) {
            k1 += 64; u1 -= 16;
            lda(3, false);
#pragma unroll
            for (int m = 0; m < HI; m++) {
                if (m >= LO) mma_bf(acc[m], a[0][0], a[0][1], a[0][2], a[0][3], b[m >> 1][2 * (m & 1)], b[m >> 1][2 * (m & 1) + 1]);
                if (((m & 1) || m == HI - 1) && (m + 3 >= LO || last)) ldb(m >> 1);
            }
            lda(2, false); lda(1, false); lda(0, false);
#pragma unroll
            for (int j1 = 3; j1 > 0; j1--)
#pragma unroll
                for (int m = last; m + j1 < HI; m++)
                    if (m + j1 >= LO) mma_bf(acc[m + j1 + (!LO && j1 >= SPLITJ && m + j1 >= SPLITM ? 8 : 0)], a[j1][0], a[j1][1], a[j1][2], a[j1][3], b[m >> 1][2 * (m & 1)], b[m >> 1][2 * (m & 1) + 1]);
        };
        if (AM & 1) for (int j1 = 1; j1 < 4; j1++) a[j1][1] = lds32(k1 + 512 * j1 + 32);
#pragma unroll
        for (int j0 = 0; j0 < 8; j0++) pass(j0 == 7);
        if (!LO) {
#pragma unroll
            for (int i = SPLITM; i < HI; i++) { acc[i][0] += acc[i + 8][0]; acc[i][1] += acc[i + 8][1]; acc[i][2] += acc[i + 8][2]; acc[i][3] += acc[i + 8][3]; }
        }
        c2 = lds128(ct + 1024);
#pragma unroll
        for (int m = LO ? LO : 1; m < HI; m++) mma_bf(acc[m], a[0][0], a[0][1], a[0][2], a[0][3], b[m >> 1][2 * (m & 1)], b[m >> 1][2 * (m & 1) + 1]);
        if (HI > 8) {
            const uint32_t kv = __byte_perm(lds32(kt + KT_P4 + 140 * 4), 0, 0x1010), e0 = kv & c2.x, e1 = kv & c2.y;
            const uint32_t e3 = e0 + oz, e4 = e1 + oz, z2 = oz + oz;
            uint32_t f[2][4];
            ldsm4(f[0], ut + c2.w); ldsm4(f[1], ut + c2.w + 512);
#pragma unroll
            for (int m = 1; m < 9; m++) mma_bf(acc[m + 7], e0, e1, oz, e3, b[m >> 1][2 * (m & 1)], b[m >> 1][2 * (m & 1) + 1]);
#pragma unroll
            for (int m = 0; m < 8; m++) mma_bf8(acc[m + 8], e4, z2, f[m >> 2][m & 3]);
        }
    }
    if (LO) { }
    uint32_t kb[5][4];
#pragma unroll
    for (int l = 0; l < 5; l++) if (l + 3 < HI) { const uint4 x = lds128(kt + c2.z + 128 * l); kb[l][0] = x.x; kb[l][1] = x.y; kb[l][2] = x.z; kb[l][3] = x.w; }
    const uint4 c3 = lds128(ct + 1536);
    const uint2 c4 = lds64(ct + 2048), c5 = LO ? lds64(ct + 3584) : c4;
    const uint32_t w0 = c3.x, w1 = c3.y, w2 = c3.z, w3 = c3.w, a0 = ut + c4.x, a1 = ut + c4.y;
    auto emit = [&](int q) {
        const uint32_t y0 = pack_bf16(acc[2 * q][0], acc[2 * q][1]), y1 = pack_bf16(acc[2 * q][2], acc[2 * q][3]);
        const uint32_t y2 = pack_bf16(acc[2 * q + 1][0], acc[2 * q + 1][1]), y3 = pack_bf16(acc[2 * q + 1][2], acc[2 * q + 1][3]);
        if (LO) st_async128(c5.x + out + q * OUT_STAGE, y0, y1, y2, y3, c5.y + 8 * q);
        else stsm4t(out + 512 * q, y0, y1, y2, y3);
    };
    uint32_t x[12][4];
    auto load = [&](int j) { x[j][0] = lds32(a0 + 128 * j - 16); x[j][1] = lds32(a1 + 128 * j - 16); x[j][2] = lds32(a0 + 128 * j); x[j][3] = lds32(a1 + 128 * j); };
    {
        float Z[4] = {0.f, 0.f, 0.f, 0.f};
        mma_bf8(Z, w2, w3, lds32(a1 - 128));
        const uint32_t z5 = pack_bf16(Z[0], Z[1]);
#pragma unroll
        for (int l = 0; l < 5; l++) if (3 + l >= LO && 3 + l < HI) mma_bf8(acc[3 + l], oz * 3, z5, kb[l][0]);
    }
    if (HI > 4) load(0);
    if (HI > 5) load(1);
    if (!LO) { __syncwarp(); emit(0); emit(1); }
    uint32_t W[12][8];
#pragma unroll
    for (int j = 0; j + 4 < HI; j++) {
        if (LO) {
            if (j == JBAR) bar_sync(2 + (warp & 3), 64);
            if (j + 2 < 11) load(j + 2);
            if (j == 10) load(11);
        }
        float X[4], Y[4], Z[4];
        mma_bf0(X, w0, w1, w2, w3, x[j][0], x[j][1]); mma_bf0(Y, w0, w1, w2, w3, x[j][1] + oz, x[j][2] + oz); mma_bf0(Z, w0, w1, w2, w3, x[j][2], x[j][3]);
        W[j][0] = pack_bf16(Y[0], Y[1]); W[j][1] = pack_bf16(Z[0], Z[1]); W[j][2] = pack_bf16(Y[2], Y[3]); W[j][3] = pack_bf16(Z[2], Z[3]);
        W[j][4] = pack_bf16(X[0], X[1]); W[j][5] = W[j][0] + oz; W[j][6] = pack_bf16(X[2], X[3]); W[j][7] = W[j][2] + oz;
#pragma unroll
        for (int i = 0; i <= j; i++)
#pragma unroll
            for (int h = 0; h < 2; h++)
#pragma unroll
                for (int l = 0; l < 5; l++) {
                    const int m = i + 4 + l, when = max(i, (m & ~1) - 4 - LOOK + (LOOK < 4 ? (i & 1) : 0));
                    if (when == j && m < HI && m >= LO) mma_bf(acc[m], W[i][4 * h], W[i][4 * h + 1], W[i][4 * h + 2], W[i][4 * h + 3], kb[l][2 * h], kb[l][2 * h + 1]);
                }
        if (((j & 1) || j + 5 == HI) && j + 4 >= LO) emit(2 + (j >> 1));
    }
}

__device__ __forceinline__ void conv_warp(int lane, uint32_t sb, int warp, const uint32_t (&q)[8][4], uint4 k8) {
    const uint32_t kt = sb + SC_KT + warp * KT_BYTES;
    float acc[16][4];
    const uint32_t a8 = kt + KT_P8 + (6 + 32 * (lane & 3) + (lane >> 2)) * 4;
    sts32(a8, k8.x); sts32(a8 + 32, k8.y); sts32(a8 + 64, k8.z); sts32(a8 + 96, k8.w);
    __syncwarp();
#pragma unroll
    for (int l = 0; l < 8; l++) {
        const uint2 kb = lds64(kt + KT_P8 + (3 + 8 * l + (lane >> 2) - (lane & 3)) * 8);
#pragma unroll
        for (int j = 0; j < 8 - l; j++) {
            if (l == 0) mma_bf0(acc[8 + j], q[j][0], q[j][1], q[j][2], q[j][3], kb.x, kb.y);
            else mma_bf(acc[8 + j + l], q[j][0], q[j][1], q[j][2], q[j][3], kb.x, kb.y);
        }
    }
    asm volatile("setmaxnreg.inc.sync.aligned.u32 168;");
    if (warp < 4) { bar_sync(6 + warp, 64); mbar_wait(sb + SB_UT + 8); }
    conv_core<NL, 16>(acc, sb, warp, kt, sb + SC_UT + warp * UT_STRIDE + 128, sb + SC_CT + lane * 16, warp * 288);
}

template <int ADD>
__device__ __forceinline__ void put_row(void* op, const uint32_t (&o)[4], uint32_t on) {
    if (ADD) asm volatile("{ .reg .pred p; setp.ne.u32 p, %5, 0; @p red.relaxed.gpu.global.add.noftz.v4.bf16x2 [%0], {%1, %2, %3, %4}; }"
                          :: "l"(op), "r"(o[0]), "r"(o[1]), "r"(o[2]), "r"(o[3]), "r"(on) : "memory");
    else asm volatile("{ .reg .pred p; setp.ne.u32 p, %5, 0; @p st.global.v4.b32 [%0], {%1, %2, %3, %4}; }" :: "l"(op), "r"(o[0]), "r"(o[1]), "r"(o[2]), "r"(o[3]), "r"(on) : "memory");
}

__device__ __forceinline__ void conv_low(int lane, const Params& p, uint32_t sb, int slab, int warp, uint32_t t0, uint4 (&x)[4]) {
    const uint32_t kt = sb + SH_KT + warp * KH_BYTES;
    mbar_wait(sb + FB_UT);
    if (lane < 11) sts128(kt + 16 * (lane < 4 ? lane : 128 + lane), 0, 0, 0, 0);
    __syncwarp();
    if (warp < 4) sleep_until<100>(t0 + KDELAY3);
#pragma unroll 1
    for (int c = warp;; c ^= 12) {
        kfetch<3>(lane, p, 16 * slab + c, lds32(sb + SF_TK), x);
        kstore(lane, x, kt, sb + SH_CT);
        x[1].w = 0;
        if (c < 8 && clk() - t0 >= (warp < 4 ? KDELAY4 : KDELAY2)) kissue<3>(lane, p, 16 * slab + (c ^ 12), x);
        __syncwarp();
        float acc[16][4];
        conv_core<0, NL>(acc, sb, warp, kt, sb + SH_UT + c * UH_STRIDE + 4 * (c & 8) + 128, sb + SH_CT + lane * 16, (c < 8 ? sb + SH_OUT + c * OH_STRIDE : kt + 32) + lane * 16);
        if (c >= 8) break;
    }
    __syncwarp();
    if (warp < 8 - NOUT) bar_arrive(13, 320);
}

__device__ __forceinline__ void mixed_output(int lane, const Params& p, uint32_t sb, int slab, int warp, bool dry) {
    const int t = lane & 3, mi = lane >> 3, r8 = lane & 7, h = warp & 1, q0 = (warp >> 1) & (NOUT / 2 - 1);
    if (warp >= 8 && !dry) {
        const uint32_t tag = lds32(sb + SF_TK), tg = tag << 14;
        const int i = 96 * h + lane;
        uint4 r[3];
        for (int it = 0;;) {
            uint32_t bad = 0;
#pragma unroll
            for (int k = 0; k < 3; k++) r[k] = ld_rlx128(&p.scr->rec[4 * i + 128 * k]);
            const uint32_t z = ld_acq32(&p.scr->zero[8 * (2 * slab + h)]);
#pragma unroll
            for (int k = 0; k < 3; k++) bad |= (r[k].x ^ tg) | (r[k].y ^ tg) | (r[k].z ^ tg) | (r[k].w ^ tg);
            if ((bad & 0xc000u) == 0 && z == tag) break;
            POLL_GUARD(it);
        }
        mbar_wait(sb + FB_GU);
#pragma unroll
        for (int k = 0; k < 3; k++) sts128(sb + SF_XS + 16 * i + 512 * k, r[k].x, r[k].y, r[k].z, r[k].w);
        __syncwarp();
        bar_arrive(13, 320);
        return;
    }
    int row = 32 * q0 + 8 * (lane & 2) + 8 * h + (lane >> 2);
    const int cl = 2 * mi + (r8 & 1);
    uint32_t ua = sb + SH_UT + cl * UH_STRIDE + ((r8 & 2) ? UH_HI : 0) + 128 + h * UH_PL + 16 * (r8 >> 2) + 32 * q0;
    uint32_t ya = sb + ((r8 & 2) ? SH_KT + 32 + (cl ^ 4) * KH_BYTES : SH_OUT + cl * OH_STRIDE) + h * 128 + 16 * (r8 >> 2) + 32 * q0;
    __nv_bfloat16* op = p.out + row * DM + 16 * slab + 8 * (t & 1);
    if (!dry) bar_sync(13, 320);
    const uint32_t thr = key_thr(lds32(sb + SF_SEL + 28));
#pragma unroll 1
    for (int q = 0; q < 8 / NOUT; q++, row += 16 * NOUT, ua += 16 * NOUT, ya += 16 * NOUT, op += 16 * NOUT * DM) {
        uint32_t r[NL], u[NL][4], y[NL][4], routed = 0;
#pragma unroll
        for (int i = 0; i < NL; i++) { r[i] = lds32(sb + SF_XS + 4 * row + 512 * i); ldsm4t(u[i], ua + 128 * i); ldsm4t(y[i], ya + 256 * i); }
#pragma unroll
        for (int i = 0; i < NL; i++) {
            const uint32_t gg = __byte_perm(r[i], 0, 0x1010) & 0x3fff3fffu;
            uint32_t om = hsub2(0x3f803f80u, gg);
            const bool add = ((r[i] & 0xffff0000u) | (uint32_t)(2047 - 128 * i - row)) >= thr;
            if (add) { om = 0; routed |= 1 << i; }
#pragma unroll
            for (int k = 0; k < 4; k++) y[i][k] = hfma2(gg, y[i][k], hmul2(om, u[i][k]));
            put_row<0>(op + 128 * i * DM, y[i], !(dry || add));
        }
        if (routed && !dry) {
#pragma unroll
            for (int i = 0; i < NL; i++) put_row<1>(op + 128 * i * DM, y[i], 1 & (routed >> i));
        }
        __syncwarp();
    }
}

__device__ __forceinline__ uint32_t utile_addr(uint32_t sb, int row, int c8) {
    return sb + SC_UTILE + (row >> 9) * 8192 + (((row >> 4) & 3) + 4 * (row & 1) + 8 * ((row >> 7) & 3) + 32 * ((row >> 1) & 7)) * 32 + ((c8 ^ row) & 1) * 16;
}

__device__ __forceinline__ void conv_helper(int lane, const Params& p, const CUtensorMap* mU, uint32_t sb, int cb, int hw, uint32_t t0) {
    const int g = lane >> 2, t = lane & 3, mi = lane >> 3, r8 = lane & 7;
    const int rank = cb & 1, slab = cb >> 1;
    const uint32_t bar_out = sb + SB_OUT;
    asm volatile("setmaxnreg.dec.sync.aligned.u32 88;");
    uint32_t tag = 0;
    if (elect()) {
        const uint32_t b = sb + SC_BAR + 8 * hw;
        mbar_init(b, hw < 4 ? 1 : 9); mbar_init(bar_out + 8 * hw, 1);
        mbar_fence_init();
        if (hw < 6) mbar_expect(b, hw == 4 ? 8192 + sizeof(Consts) : 8192);
        if (hw == 4) bulk_load(sb + SC_CT, p.consts, sizeof(Consts), b);
        if (hw < 4) {
            if (hw >= 2) spin_until(t0, VDELAY);
            tma5d(sb + SC_UTILE + hw * 8192, mU, 16 * slab, 4 * rank, 0, 4 * hw, 0, b);
        }
        mbar_expect(bar_out + 8 * hw, 4096);
        if (hw == 4) tag = take_ticket(&p.scr->launch);
    }
    __syncwarp();
    cluster_arrive_relaxed();
    if (lane < 16) sts128(sb + SC_UT + hw * UT_STRIDE + mi * UT_PL + r8 * 16, 0, 0, 0, 0);
    if (lane < 17) sts128(sb + SC_KT + hw * KT_BYTES + 16 * (lane < 4 ? lane : lane < 11 ? 128 + lane : 164 + lane), 0, 0, 0, 0);
    if (hw == 7) sts64(sb + SC_CT + 3584 + lane * 16, mapa(sb + SC_OUT + rank * OUT_HALF + g * 32 + (t & 1) * 16, t >> 1), mapa(bar_out, t >> 1));
    if (hw == 4) { tag = tag_of(__reduce_max_sync(0xffffffffu, tag)); sts32(sb + SC_TAG, tag); }
    cluster_wait();
    {
        const int box = hw >> 2, h = hw & 1, k0 = hw & 2;
        const uint32_t src = sb + SC_UTILE + box * 8192 + h * 4096 + k0 * 256 + (32 * mi + (r8 >> 1) + 4 * (r8 & 1)) * 32;
        const uint32_t so = ((rank ^ r8) & 1) << 4;
        const uint32_t dst = sb + SC_UT + g * UT_STRIDE + 128 + h * UT_PL + k0 * 128 + (32 * box + 4 * rank + t) * 16;
        const uint32_t rdst = mapa(dst, rank ^ 1), rbar = mapa(sb + SB_UT, rank ^ 1);
#pragma unroll 1
        for (int i = 0; i < 2; i++) {
            mbar_wait(sb + SC_BAR + 8 * box + 16 * i);
            const uint32_t ts = clk();
            uint32_t a[2][4], b[2][4];
#pragma unroll
            for (int k = 0; k < 2; k++) { ldsm4t(a[k], src + (so ^ 16) + k * 256 + i * 16384); ldsm4t(b[k], src + so + k * 256 + i * 16384); }
#pragma unroll
            for (int k = 0; k < 2; k++) sts128(dst + k * 128 + i * 1024, b[k][0], b[k][1], b[k][2], b[k][3]);
#pragma unroll
            for (int k = 0; k < 2; k++) {
                if (k == 0) { __syncwarp(); if (lane == 0) mbar_arrive(sb + SB_UT + 8 * i); }
                spin_until(ts, (hw + 8 * k) * PACE);
                st_async128(rdst + k * 128 + i * 1024, a[k][0], a[k][1], a[k][2], a[k][3], rbar + 8 * i);
            }
        }
    }
}

__device__ __forceinline__ void conv_output(int lane, const Params& p, uint32_t sb, int cb, int hw, uint32_t t0, bool dry) {
    const int g = lane >> 2, t = lane & 3, mi = lane >> 3, r8 = lane & 7;
    const int rank = cb & 1, slab = cb >> 1;
    const uint32_t bar_out = sb + SB_OUT, s_key = sb + SC_KEY;
    if (hw == 5) {
        uint32_t tn = t0 + WDELAY + 3 * WPER0 + 6 * WPER;
        sleep_until<300>(tn - 800);
        const int q = 72 * lane + cb, i = q / 120, r = q % 120, od = (i < 4 ? 4 * (r & ~3) + 4 * i + (r & 3) : q) * 4608;
#pragma unroll 1
        for (int n = 0; n < 8; n++, tn += DPER) {
            const int o = __shfl_sync(0xffffffffu, od, n);
            sleep_until<20>(tn);
            if (elect()) prefetch_l2(p.wd + o, 9216);
        }
        return;
    }
    if (hw == 4) {
        const uint32_t tag = lds32(sb + SC_TAG);
        uint32_t key;
        sleep_until<400>(t0 + SDELAY);
        for (int it = 0;;) {
            key = ld_rlx32(&p.scr->sel[g]);
            if (__all_sync(0xffffffffu, key >> 29 == tag)) break;
            POLL_GUARD(it);
            __nanosleep(200);
        }
        if (lane == 31) sts32(s_key, key);
        bar_arrive(1, 224);
        const int row = key_row(key);
        if (((row >> 6) & 1) == rank) asm volatile("st.relaxed.gpu.global.v2.b32 [%0], {%1, %1};" :: "l"(p.out + row * DM + 16 * slab + 4 * t), "r"(0) : "memory");
        __syncwarp();
        asm volatile("fence.acq_rel.gpu;" ::: "memory");
        if (lane < 8) st_rlx32(&p.scr->zero[8 * cb + lane], tag);
        bar_arrive(10, 224);
        return;
    }
    if (!dry) bar_sync(1, 224);
    const uint32_t last = lds32(s_key), tg = last >> 29 << 14;
    const int st = 2 + min(hw >> 1, 2), i0 = 4 * (hw & 1);
    const int row = 256 * st + 128 * (g >> 2) + 64 * rank + 32 * (t >> 1) + 16 * (g & 1) + 8 * ((g >> 1) & 1) + i0;
    uint4 r[2];
    r[0] = r[1] = make_uint4(tg, tg, tg, tg);
    for (int it = 0;;) {
        if (!dry) { r[0] = ld_rlx128(&p.scr->rec[row]); r[1] = ld_rlx128(&p.scr->rec[row + 768]); }
        if ((((r[0].x ^ tg) | (r[0].y ^ tg) | (r[0].z ^ tg) | (r[0].w ^ tg) | (r[1].x ^ tg) | (r[1].y ^ tg) | (r[1].z ^ tg) | (r[1].w ^ tg)) & 0xc000u) == 0) break;
        POLL_GUARD(it);
    }
    __syncwarp();
    const uint32_t thr = key_thr(last);
    const uint32_t ya = sb + SC_OUT + st * OUT_STAGE + ((r8 >> 1) & 1) * OUT_HALF + (2 * mi + (r8 & 1)) * 288 + (2 * i0 + (r8 >> 2)) * 16;
    __nv_bfloat16* const op = p.out + row * DM + 16 * slab + 8 * (t & 1);
    uint32_t gg[8], o[8][4], routed = 0;
#pragma unroll
    for (int k = 0; k < 2; k++) {
        const uint32_t rr[4] = {r[k].x, r[k].y, r[k].z, r[k].w}, ua = utile_addr(sb, row + 768 * k, t & 1);
#pragma unroll
        for (int i = 0; i < 4; i++) {
            const int n = 4 * k + i;
            gg[n] = __byte_perm(rr[i], 0, 0x1010) & 0x3fff3fffu;
            uint32_t om = hsub2(0x3f803f80u, gg[n]);
            if (((rr[i] & 0xffff0000u) | (uint32_t)(2047 - 768 * k - i - row)) >= thr) { om = 0; routed |= 1 << n; }
            const uint4 u4 = lds128((ua ^ ((i & 1) * 16)) + (i & 1) * 128 + (i >> 1) * 1024);
            o[n][0] = hmul2(om, u4.x); o[n][1] = hmul2(om, u4.y); o[n][2] = hmul2(om, u4.z); o[n][3] = hmul2(om, u4.w);
        }
    }
    const uint32_t on = dry ? 0 : row >= 128 * NL ? 0xff : 0xf0;
    if (!dry) bar_sync(10, 224);
#pragma unroll 1
    for (int once = blockIdx.y; once < 1; once++) {
#pragma unroll
        for (int k = 0; k < 2; k++) {
            if (!dry && 2 * st + 6 * k + 1 >= NL) mbar_wait(bar_out + 8 * st + 24 * k);
            uint32_t y[4][4];
#pragma unroll
            for (int i = 0; i < 4; i++) ldsm4t(y[i], ya + 3 * k * OUT_STAGE + 32 * i);
#pragma unroll
            for (int i = 0; i < 4; i++) {
#pragma unroll
                for (int e = 0; e < 4; e++) y[i][e] = hfma2(gg[4 * k + i], y[i][e], o[4 * k + i][e]);
                put_row<0>(op + (768 * k + i) * DM, y[i], on & ~routed & (1 << (4 * k + i)));
            }
            if (on & routed & (15 << 4 * k)) {
#pragma unroll
                for (int i = 0; i < 4; i++) put_row<1>(op + (768 * k + i) * DM, y[i], routed & (1 << (4 * k + i)));
            }
            __syncwarp();
        }
    }
}

struct Maps { const CUtensorMap *U2, *R, *G64, *Wd; };
struct WMaps { CUtensorMap m[4]; };

__device__ __forceinline__ void load_weights(const Params& p, const Maps& m, uint32_t sb, int f, bool pure, int n, int n1, uint32_t& tn) {
#pragma unroll 1
    for (; n < n1; n++) {
        const uint32_t b = sb + FB_W + 8 * n, d = sb + n * (pure ? PIECE_P : PIECE_H);
        if (n >= (pure ? 3 : 4)) mbar_wait(n < 4 ? sb + FB_SEL : n < 9 ? sb + FB_KG : n < 13 ? sb + FB_FREE : sb + FB_FREE + 8);
        sleep_until<30>(tn);
        tn += n < 3 ? WPER0 : n < 9 ? WPER : DPER * 5 / 3;
        __syncwarp();
        if (elect()) {
            mbar_expect(b, n >= 9 ? DPIECE : pure ? PIECE_P : PIECE_H);
            if (n == 9) mbar_arrive_peer(mapa(sb + FB_PEER, 1));
            if (n >= 9) tma3d(d - 9 * PIECE_P, m.Wd, 0, n < 13 ? 64 * f + 32 * n - 288 : 16 * f + 3840, 0, b);
            else {
#pragma unroll 1
                for (int i = pure ? 3 : 1; i >= 0; i--) tma2d(d + 4096 * (i + min(i, 2)), m.G64 + i, i < 2 ? 64 * f : 3840 + 16 * f, 64 * n, b);
            }
        }
    }
}

__device__ __forceinline__ void above(uint4 x, uint32_t m, uint32_t& a, uint32_t& b) {
    asm("{ .reg .u32 p, q, r, s; mad.lo.u32 p, %2, -1, %6; mad.lo.u32 q, %3, -1, %6; mad.lo.u32 r, %4, -1, %6; mad.lo.u32 s, %5, -1, %6;"
        "shr.u32 p, p, 31; shr.u32 q, q, 31; shr.u32 r, r, 31; shr.u32 s, s, 31; add.u32 %0, %0, p; add.u32 %1, %1, q; add.u32 %0, %0, r; add.u32 %1, %1, s; }"
        : "+r"(a), "+r"(b) : "r"(x.x), "r"(x.y), "r"(x.z), "r"(x.w), "r"(m));
}
__device__ __forceinline__ void select_rows(int lane, const Params& p, uint32_t sb, int f, int sw, uint32_t tag, uint32_t t0) {
    const int tid = 32 * sw + lane;
    uint4 k[6];
    uint32_t qm[6];
    const uint32_t ca = sb + SF_CNT + (lane & blockIdx.y);
    tag <<= 29;
    k[5] = make_uint4(tag, tag, tag, tag);
    sts128(sb + SF_LIST + tid * 16, 0, 0, 0, 0); sts128(sb + SF_LIST + 1536 + tid * 16, 0, 0, 0, 0); sts128(sb + SF_LIST + 2560 + tid * 16, 0, 0, 0, 0);
    sleep_until<40>(t0 + PDELAY);
    bool bad[6] = {true, true, true, true, true, sw == 0};
    for (int it = 0;;) {
#pragma unroll
        for (int i = 0; i < 6; i++) if (bad[i]) k[i] = ld_rlx128(&p.scr->rec[L_SEQ + 384 * i + 4 * tid]);
#pragma unroll
        for (int i = 0; i < 6; i++) {
            qm[i] = max(__vimax3_u32(k[i].x, k[i].y, k[i].z), k[i].w);
            bad[i] = ((min(__vimin3_u32(k[i].x, k[i].y, k[i].z), k[i].w) ^ tag) | (qm[i] ^ tag)) >= 0x20000000u;
        }
        if (!__any_sync(0xffffffffu, bad[0] | bad[1] | bad[2] | bad[3] | bad[4] | bad[5])) break;
        POLL_GUARD(it);
    }
    {
        uint32_t mx[6];
#pragma unroll
        for (int i = 0; i < 6; i++) mx[i] = __reduce_max_sync(0xffffffffu, qm[i]);
        sts128(sb + SF_MAX + 16 * sw, mx[0], mx[1], mx[2], mx[3]); sts32(sb + SF_MAX + 48 + 4 * sw, mx[4]);
        if (sw == 0) sts32(sb + SF_MAX + 60, mx[5]);
    }
    bar_sync(8, 96);
    uint32_t thr;
    {
        const uint32_t m = lds32(sb + SF_MAX + (lane & 15) * 4);
        const uint4 x = lds128(sb + SF_MAX + 2 * (lane & 16)), y = lds128(sb + SF_MAX + 2 * (lane & 16) + 16);
        uint32_t rk = 0, r2 = 0;
        above(x, m, rk, r2); above(y, m, rk, r2);
        rk += r2;
        thr = __reduce_max_sync(0xffffffffu, rk + __shfl_xor_sync(0xffffffffu, rk, 16) == 7 ? m : 0u);
    }
    uint32_t pos = 0;
    uint32_t cnt = (thr - 1 - qm[4]) >> 31, c2 = (thr - 1 - qm[5]) >> 31;
    above(make_uint4(qm[0], qm[1], qm[2], qm[3]), thr - 1, cnt, c2);
    cnt = 16 * (cnt + c2);
    asm volatile("{ .reg .pred p; setp.ne.u32 p, %2, 0; @p atom.shared.add.u32 %0, [%1], %2; }" : "+r"(pos) : "r"(ca), "r"(cnt) : "memory");
#pragma unroll
    for (int i = 0; i < 6; i++) if (qm[i] >= thr) { sts128(sb + SF_LIST + pos, k[i].x, k[i].y, k[i].z, k[i].w); pos += 16; }
    bar_sync(8, 96);
    const int n = lds32(sb + SF_CNT);
    uint32_t m, rk;
    int base = 0;
#pragma unroll 1
    do {
        m = lds32(sb + SF_LIST + base + 12 * (lane & 28) + 16 * sw + 4 * (lane & 3));
        rk = 0;
        uint32_t r2 = 0;
        int i = 0;
#pragma unroll 1
        do {
            uint4 x[6];
#pragma unroll
            for (int e = 0; e < 6; e++) x[e] = lds128(sb + SF_LIST + i + 16 * e);
#pragma unroll
            for (int e = 0; e < 6; e++) above(x[e], m, rk, r2);
        } while ((i += 16 * 6) < n);
        rk += r2;
        if (rk < 8) sts32(sb + SF_SEL + 4 * rk, m);
    } while ((base += 384) < n);
    if (RARE(n > 384)) {
        bar_sync(8, 96);
        rk = tid; m = lds32(sb + SF_SEL + 4 * (lane & 7));
    }
    if (rk < 8) {
        mbar_expect(sb + FB_X, 1152);
        bulk_load(sb + SF_XS + 1168 * rk, p.u + key_row(m) * DM, 1152, sb + FB_X);
        if (f == 0) st_rlx32(&p.scr->sel[rk], m);
    }
    __syncwarp();
}

__device__ __forceinline__ bool ffn_worker(int lane, const Params& p, const Maps& m, uint32_t sb, int f, bool pure, int gw, uint32_t t0, uint32_t tag, uint32_t tn) {
    const int mi = lane >> 3, r8 = lane & 7, kr = 8 * (mi >> 1) + r8;
    const uint32_t sh = sb + (pure ? SP_H : SH_H);
    uint4* const pdst = p.scr->part + ((12 * (f & 1) + 2 * gw) * 30 + (f >> 1)) * 32 + lane;
    {
        const int piece = pure ? PIECE_P : PIECE_H;
        const uint32_t ws = gw < 8 ? 2048 : 1024, xa = sb + SF_XS + r8 * 1168 + mi * 16;
        const uint32_t wa = (gw < 8 ? sb + kr * 128 + ((gw ^ r8) << 4) : sb + 16384 + kr * 64 + (((gw ^ (r8 >> 1)) & 3) << 4)) + (mi & 1) * 4 * ws;
        uint32_t a[9][4][4];
        auto fetch = [&](int n) {
            mbar_wait(sb + FB_W + 8 * n);
#pragma unroll
            for (int s = 0; s < 4; s++) ldsm4t(a[n][s], wa + n * piece + s * ws);
        };
        auto release = [&](int n) {
            asm volatile("" :: "r"(a[n][0][0]), "r"(a[n][1][0]), "r"(a[n][2][0]), "r"(a[n][3][0]) : "memory");
            __syncwarp();
            if (lane == 0) mbar_arrive(sb + FB_FREE + 4 * (n - 3));
        };
        auto clear = [&]() { if (gw < 6) { st_pkt(pdst, 0, 0, 0, 0); st_pkt(pdst + 30 * 32, 0, 0, 0, 0); } };
        fetch(0); fetch(1); fetch(2); fetch(3); release(3);
        fetch(4); fetch(5); release(5);
        if (!pure && gw == 5) {
            mbar_wait(sb + FB_FREE + 8);
            sleep_until<30>(tn);
            __syncwarp();
            if (elect()) {
#pragma unroll 1
                for (int i = 0; i < (f < 48 ? 5 : 4); i++) {
                    mbar_expect(sb + FB_D + 8 * i, DPIECE);
                    tma3d(sb + i * DPIECE, m.Wd, 0, i < 4 ? 64 * (f & ~1) + 32 * i : 16 * f + 3824, 9 * (f & 1), sb + FB_D + 8 * i);
                }
            }
        }
        mbar_wait(sb + FB_X);
        float c[4][4] = {};
#pragma unroll
        for (int n = 0; n < 9; n++) {
            uint32_t x[2][4];
            ldsm4(x[0], xa + 128 * n); ldsm4(x[1], xa + 128 * n + 64);
            if (n >= 2 && n < 5) fetch(n + 4);
#pragma unroll
            for (int s = 0; s < 4; s++) mma_bf(c[s], a[n][s][0], a[n][s][1], a[n][s][2], a[n][s][3], x[s >> 1][2 * (s & 1)], x[s >> 1][2 * (s & 1) + 1]);
        }
        const float g0 = rbf((c[0][0] + c[1][0]) + (c[2][0] + c[3][0])), g1 = rbf((c[0][1] + c[1][1]) + (c[2][1] + c[3][1]));
        const float u0 = rbf((c[0][2] + c[1][2]) + (c[2][2] + c[3][2])), u1 = rbf((c[0][3] + c[1][3]) + (c[2][3] + c[3][3]));
        uint32_t hp = pack_bf16(rbf(g0 * sigmoidf_(g0)) * u0, rbf(g1 * sigmoidf_(g1)) * u1);
        asm volatile("movmatrix.sync.aligned.m8n8.trans.b16 %0, %0;" : "+r"(hp));
        const uint32_t ho = ((gw >> 1) + 4 * ((f & 1) | (gw >> 3))) * 256 + lane * 8 + (gw & 1) * 4;
        const bool pp = f < 48 && !pure;
        if (f < 48) mbar_wait(sb + (pure ? FB_FREE + 8 : FB_PEER));
        st_async32(mapa(sb + (pp ? SP_H : SH_H) + ho, ~f & 1), hp, mapa(sb + FB_GU, ~f & 1));
        sts32(sh + ho, hp);
        __syncwarp();
        if (lane == 0) mbar_arrive(sb + FB_GU);
        clear();
    }
    if (gw < 6) {
        uint32_t off[3], w[2][6][4];
#pragma unroll
        for (int k = 0; k < 3; k++) off[k] = sb + ((3 * gw + k) >> 1) * 2048 + kr * 64 + ((((2 * (gw + k) + (mi & 1)) ^ (r8 >> 1)) & 3) << 4);
        float d[6][4] = {};
        auto dfetch = [&](int i) {
            mbar_wait(sb + FB_D + 8 * i);
#pragma unroll
            for (int k = 0; k < 6; k++) ldsm4t(w[i & 1][k], off[k % 3] + k / 3 * 1024 + i * (pure ? PIECE_P : DPIECE));
        };
        uint2 hv[10];
        auto dmult = [&](int i) {
#pragma unroll
            for (int k = 0; k < 6; k++) mma_bf(d[k], w[i & 1][k][0], w[i & 1][k][1], w[i & 1][k][2], w[i & 1][k][3], hv[2 * i + k / 3].x, hv[2 * i + k / 3].y);
        };
        dfetch(0); dfetch(1);
        mbar_wait(sb + FB_GU);
#pragma unroll
        for (int i = 0; i < 10; i++) hv[i] = lds64(sh + lane * 8 + i * 256);
        dmult(0); dfetch(2); dmult(1); dfetch(3); dmult(2);
        if (f < 48) { dfetch(4); dmult(3); dmult(4); } else dmult(3);
        auto word = [&](int k) { return pack_bf16(d[k >> 1][2 * (k & 1)] + d[3 + (k >> 1)][2 * (k & 1)], d[k >> 1][2 * (k & 1) + 1] + d[3 + (k >> 1)][2 * (k & 1) + 1]); };
#pragma unroll
        for (int k = 0; k < 2; k++) st_pkt(pdst + k * 30 * 32, word(3 * k), word(3 * k + 1), word(3 * k + 2), tag);
        if (pure) bar_arrive(13, 384);
        return false;
    }
    return true;
}

__device__ __forceinline__ void ffn_gather(int lane, const Params& p, uint32_t sb, int idx, int gw) {
    const uint4* src = p.scr->part + (idx * 30 + 5 * gw - 30) * 32 + lane;
    uint4 v[5] = {};
#pragma unroll 1
    for (uint32_t tag = 0;;) {
        for (int it = 0; ((v[0].w ^ tag) | (v[1].w ^ tag) | (v[2].w ^ tag) | (v[3].w ^ tag) | (v[4].w ^ tag)) != 0;) {
#pragma unroll
            for (int k = 0; k < 5; k++) if (v[k].w != tag) v[k] = ld_pkt(src + k * 32);
            POLL_GUARD(it);
        }
        float s[6] = {};
#pragma unroll
        for (int k = 0; k < 5; k++) { s[0] += bf_lo(v[k].x); s[1] += bf_hi(v[k].x); s[2] += bf_lo(v[k].y); s[3] += bf_hi(v[k].y); s[4] += bf_lo(v[k].z); s[5] += bf_hi(v[k].z); }
#pragma unroll
        for (int k = 0; k < 3; k++) sts64(sb + SP_RED + gw * 768 + k * 256 + lane * 8, __float_as_uint(s[2 * k]), __float_as_uint(s[2 * k + 1]));
        __syncwarp();
        if (tag) break;
        tag = lds32(sb + SF_TK);
        bar_sync(13, 384);
        spin_until(clk(), GDELAY);
    }
    bar_arrive(12, 288);
}

__device__ __forceinline__ void ffn_final(int lane, const Params& p, uint32_t sb, int idx, int warp) {
    const int r8 = lane & 7, i = 32 * max(warp - 13, 0) + lane, col = 24 * idx + 2 * (i >> 3);
    const uint32_t tag = lds32(sb + SF_TK);
    mbar_wait(sb + FB_X);
    const uint32_t key = lds32(sb + SF_SEL + 4 * r8), x = lds32(sb + SF_XS + r8 * 1168 + 2 * col);
    const int row = key_row(key);
    uint32_t rc;
    for (int it = 0;;) { rc = ld_rlx32(&p.scr->rec[row]); if (((rc >> 14) & 3u) == tag) break; POLL_GUARD(it); }
    const float om = rbf(1.f - bf_lo(rc & 0x3fffu)), rs = rbf(sigmoidf_(key_val(key)));
    __syncwarp();
#pragma unroll 1
    for (int real = 0;; real = 1) {
        float y0 = 0.f, y1 = 0.f;
#pragma unroll
        for (int k = 6; k < 12; k++) {
            const uint32_t ra = sb + SP_RED + 768 * k + (i >> 3) * 64 + r8 * 4;
            y0 += __uint_as_float(lds32(ra)); y1 += __uint_as_float(lds32(ra + 32));
        }
        uint32_t o = pack_bf16(om * rbf(bf_lo(x) + rbf(rbf(y0) * rs)), om * rbf(bf_hi(x) + rbf(rbf(y1) * rs)));
        asm volatile("" : "+r"(o));
        if (real) { red_bf2(p.out + row * DM + col, o); break; }
        mbar_wait(sb + FB_GU);
        for (int it = 0; ld_acq32(&p.scr->zero[8 * (2 * (col >> 4) + ((row >> 6) & 1))]) != tag;) POLL_GUARD(it);
        __syncwarp();
        bar_sync(12, 288);
    }
}

__device__ __forceinline__ bool ffn_cta(int lane, const Params& p, const Maps& m, uint32_t sb, int f, bool pure, int idx, int warp, uint32_t t0, uint4 (&x)[4], int ch) {
    const int g = lane >> 2, t = lane & 3, mi = lane >> 3, r8 = lane & 7;
    const int nw = pure ? 12 : 8, ng = pure ? 3 : idx < 4 ? 6 : 5;
    uint32_t tag = 0, tn = t0 + WDELAY;
    if (warp == 13) {
        if (elect()) {
            mbar_init(sb + FB_WR, 1);
            mbar_fence_init();
            mbar_expect(sb + FB_WR, 2304);
            bulk_load(sb + SF_WR, p.wr, 1152, sb + FB_WR); bulk_load(sb + SF_WR + 1152, p.gatew, 1152, sb + FB_WR);
            mbar_init(sb + FB_TK, 1);
#pragma unroll
            for (int i = 0; i < 14; i++) mbar_init(sb + FB_W + 8 * i, 1);
            mbar_init(sb + FB_FREE, nw); mbar_init(sb + FB_FREE + 8, nw);
            mbar_init(sb + FB_SEL, ng); mbar_init(sb + FB_KG, nw + ng); mbar_init(sb + FB_UT, 4); mbar_init(sb + FB_GU, nw + 1); mbar_init(sb + FB_PEER, 1); mbar_init(sb + FB_X, 8);
            mbar_fence_init();
            mbar_expect(sb + FB_GU, f < 48 && !pure ? 1536 : 1024);
            prefetch_map(m.G64); prefetch_map(m.G64 + 1); prefetch_map(m.G64 + 2); prefetch_map(m.G64 + 3); prefetch_map(m.Wd);
        }
        __syncwarp();
        cluster_arrive_relaxed();
        load_weights(p, m, sb, f, pure, 0, pure ? 14 : 9, tn);
        if (pure) return false;
        mbar_wait(sb + FB_TK);
        tag = lds32(sb + SF_TK);
    } else if (warp >= nw) {
        const int r0 = pure ? 24 * idx : 576 + 40 * idx + 8 * min(idx, 4);
        const int grp = warp == 12 ? 0 : warp > 12 ? warp - 13 : warp - 5;
        const uint32_t rows = sb + (pure ? SP_R : grp < 5 ? SH_R : SH_R5 - 5 * 9216) + grp * 9216, bar_r = sb + FB_R + 8 * grp;
        if (elect()) {
            mbar_init(bar_r, 1); mbar_fence_init(); mbar_expect(bar_r, grp < 6 ? 9216 : NL * 4096 + sizeof(Consts));
            if (grp < ng) { spin_until(t0, RDELAY); tma3d(rows, m.R, 0, r0 + 8 * grp, 0, bar_r); }
        }
        __syncwarp();
        cluster_arrive_relaxed();
        if (grp == 0 && elect()) tag = take_ticket(&p.scr->launch);
        uint32_t* rp = &p.scr->rec[r0 + 8 * grp + g + L_SEQ * (t ^ 1)];
        uint32_t wa = sb + SF_WR + ((r8 >> 1) & 1) * 1152 + (2 * mi + (r8 & 1)) * 16, ra = rows + r8 * 128 + ((mi ^ r8) << 4), ts = t ? 14 : 29, kb = t ? 0 : 2047 - r0 - 8 * grp - g;
        asm volatile("" : "+l"(rp), "+r"(wa), "+r"(ra), "+r"(ts), "+r"(kb));
        if (grp < ng && t < 2) st_rlx32(rp, 0);
        if (f == 0 && grp == 2) st_rlx32(&p.scr->sel[lane], 0);
        if (grp == 6) {
            sleep_until<50>(t0 + HDELAY);
            if (elect()) { tma5d(sb + SH_RAW, m.U2, 16 * idx, 0, 0, 0, 0, bar_r); tma5d(sb + SH_RAW + NL * 2048, m.U2, 16 * idx, 4, 0, 0, 0, bar_r);
                bulk_load(sb + SH_CT, p.consts + sizeof(Consts), sizeof(Consts), bar_r); }
        }
        __syncwarp();
        cluster_wait();
        if (grp < ng) {
            mbar_wait(sb + FB_WR);
            uint32_t wv[9][4];
#pragma unroll
            for (int k = 0; k < 9; k++) ldsm4(wv[k], wa + 128 * k);
            float c[3][4];
            const uint32_t rb2 = ra ^ 64;
            if (grp == 0 && elect()) { sts64(sb + SF_CNT, 0, tag_of(tag)); mbar_arrive(sb + FB_TK); }
            __syncwarp();
            mbar_wait(bar_r);
#pragma unroll
            for (int k = 0; k < 18; k++) {
                uint32_t a[4];
                ldsm4(a, ((k & 1) ? rb2 : ra) + (k >> 1) * 1024);
                if (k < 3) mma_bf0(c[k], a[0], a[1], a[2], a[3], wv[k >> 1][2 * (k & 1)], wv[k >> 1][2 * (k & 1) + 1]);
                else mma_bf(c[k % 3], a[0], a[1], a[2], a[3], wv[k >> 1][2 * (k & 1)], wv[k >> 1][2 * (k & 1) + 1]);
            }
            mbar_wait(sb + FB_TK);
            tag = lds32(sb + SF_TK);
            kb |= tag << ts;
            const float s = (c[0][0] + c[0][3]) + (c[1][0] + c[1][3]) + (c[2][0] + c[2][3]);
            const uint32_t sr = pack_bf16(0.f, s), rb = sr ^ ((((int)sr >> 31) & 0x7fff0000u) | 0x80000000u);
            if (ts == 29) st_rlx32(rp, (rb >> 3) | kb);
            const uint32_t rec = __shfl_up_sync(0xffffffffu, rb, 1) | kb | (pack_bf16(sigmoidf_(bf_hi(sr)), 0.f) & 0x3fffu);
            if (t == 1) st_rlx32(rp, rec);
            if (lane == 0) { mbar_arrive(sb + FB_SEL); mbar_arrive(sb + FB_KG); }
        }
        if (warp >= 12) select_rows(lane, p, sb, f, grp, tag, t0);
        else {
            const int r = warp & 1, h = (warp >> 1) & 1;
            const uint32_t src = sb + SH_RAW + r * NL * 2048 + (8 * NL * (4 * h + mi) + (r8 >> 1) + 4 * (r8 & 1)) * 32 + (r8 & 1) * 16;
            const uint32_t dst = sb + SH_UT + g * UH_STRIDE + 128 + h * UH_PL + (4 * r + t) * 16;
            uint32_t a[2 * NL][4];
            mbar_wait(sb + FB_TK);
            tag = lds32(sb + SF_TK);
            mbar_wait(sb + FB_RAW);
#pragma unroll
            for (int k = 0; k < 2 * NL; k++) ldsm4t(a[k], (src ^ (16 * (k & 1))) + (k >> 1) * 256);
            mbar_wait(sb + FB_SEL);
#pragma unroll
            for (int k = 0; k < 2 * NL; k++) sts128(dst + (k & 1) * UH_HI + (k >> 1) * 128, a[k][0], a[k][1], a[k][2], a[k][3]);
            sts128(dst - 128, 0, 0, 0, 0); sts128(dst - 128 + UH_HI, 0, 0, 0, 0);
            __syncwarp();
            if (lane == 0) mbar_arrive(sb + FB_UT);
        }
    } else {
        mbar_wait(sb + FB_TK);
        tag = lds32(sb + SF_TK);
        if (warp < nw / 2) st_pkt(p.scr->kx + ch * 128 + 96 + lane, x[3].x, x[3].y, x[3].z, __byte_perm(x[3].w, tag, 0x5410));
        else kpublish(lane, p, ch, tag, x);
        if (!pure) { conv_low(lane, p, sb, idx, warp, t0, x); return warp >= 8 - NOUT; }
    }
    if (pure && warp >= 12) return true;
    return ffn_worker(lane, p, m, sb, f, pure, pure ? warp : warp - 8, t0, tag, tn);
}

__global__ void __cluster_dims__(2, 1, 1) __launch_bounds__(NTHR, 1)
fused_kernel(const Params p, const __grid_constant__ CUtensorMap mU, const __grid_constant__ CUtensorMap mU2, const __grid_constant__ CUtensorMap mR,
             const __grid_constant__ WMaps mW, const __grid_constant__ CUtensorMap mWd) {
    extern __shared__ __align__(1024) uint8_t smem_raw[];
    const uint32_t sb = smem_u32(smem_raw);
    const uint32_t t0 = __shfl_sync(0xffffffffu, clk(), 0);
    const int bx = blockIdx.x;
    const int f = bx - FFN0, cb = bx < FFN0 ? bx : bx - NFFN;
    const bool ffn = (unsigned)f < NFFN, pure = (unsigned)f < 48 && !(f & 1);
    const int idx = !ffn ? cb >> 1 : max(f >> 1, f - 24), nch = pure ? 6 : 4, c0 = nch * idx, co = !ffn ? 8 * (bx & 1) : pure ? 12 : 4;
    const int warp = warp_id(), lane = lane_id();
    KParams kp;
    {
        const int w = threadIdx.x >> 5, h = w >= nch, c = c0 + w - nch * h;
        if (w < 2 * nch) kp = kload(p, 4 * (c & ~3) + co + (c & 3), h);
    }
    const int half = warp >= nch, j = warp - nch * half, ch = 4 * ((c0 + j) & ~3) + co + ((c0 + j) & 3);
    [&]() {
    uint32_t q[8][4];
    uint4 x[4];
    if (warp < 2 * nch) {
        const uint32_t stage = sb + (!ffn ? SC_STG : pure ? SP_STG : SH_STG), mine = stage + warp * KG_STAGE, other = stage + (half ? j : warp + nch) * KG_STAGE;
        float kv[21], fin;
        cluster_arrive_relaxed();
        kgen(lane, kp, mine, kv, fin, sb);
        ksend(lane, kv, fin, mine, half);
        if (!ffn) bar_arrive(half ? 11 + j : 2 + j, 64);
        if (ffn || half) {
            bar_sync(2 + j, 64);
            if (half) {
                krecv(lane, kv, fin, other, 0, 0); krecv(lane, kv, fin, other, 1, 4); krecv(lane, kv, fin, other, 2, 8); krecv(lane, kv, fin, other, 3, 12);
                kv[16] = kv[16] * fin + __uint_as_float(lds32(other + 2048)) + bf_lo(kp.dskip);
            } else krecv(lane, kv, fin, other, 0, 17);
            if (ffn) { __syncwarp(); if (lane == 0) mbar_arrive(sb + FB_KG); }
            if (half) kpack(lane, kv, x);
            else { x[3] = kwords8(lane, kv); x[0] = x[1] = x[2] = make_uint4(0, 0, 0, 0); }
            if (!ffn) {
                mbar_wait(sb + SB_UT);
                const uint32_t tag = lds32(sb + SC_TAG);
                kpublish(lane, p, ch, tag, x);
                kstore(lane, x, sb + SC_KT + j * KT_BYTES, sb + SC_CT);
                bar_arrive(6 + j, 64);
                conv_windows(lane, sb, warp, q);
                mbar_wait(sb + SB_UT + 8);
                sleep_until<100>(t0 + ((bx & 1) ? KDELAY1 : KDELAY0));
                x[1].w = 0;
                kfetch<4>(lane, p, ch + 4, tag, x);
                kstore(lane, x, sb + SC_KT + warp * KT_BYTES, sb + SC_CT);
                x[3].w = __byte_perm(x[3].w, x[3].z, 0x5410);
            }
        }
        if (!ffn) {
            if (!half) {
            mbar_wait(sb + SB_UT);
            conv_windows(lane, sb, warp, q);
                bar_sync(11 + j, 64);
                krecv(lane, kv, fin, other, 0, 17);
                x[3] = kwords8(lane, kv);
            }
            conv_warp(lane, sb, warp, q, x[3]);
            return;
        }
    }
    int more = 0;
    if (ffn) { const Maps m = {&mU2, &mR, mW.m, &mWd}; more = ffn_cta(lane, p, m, sb, f, pure, idx, warp, t0, x, ch); }
    else { conv_helper(lane, p, &mU, sb, cb, warp - 8, t0); more = 1; }
    if (__shfl_sync(0xffffffffu, more, 0)) {
        const int lane = lane_id();
        if (!ffn || (pure && warp == 15)) conv_output(lane, p, sb, ffn ? 0 : cb, warp - 8, t0, ffn);
        else if (!pure || warp == 14) mixed_output(lane, p, sb, idx, warp, pure);
        else if (warp < 12) ffn_gather(lane, p, sb, idx, warp);
        if (pure && warp >= 12) ffn_final(lane, p, sb, idx, warp);
    }
    }();
}

typedef CUresult (*EncodeFn)(CUtensorMap*, CUtensorMapDataType, cuuint32_t, void*, const cuuint64_t*, const cuuint64_t*, const cuuint32_t*, const cuuint32_t*,
                             CUtensorMapInterleave, CUtensorMapSwizzle, CUtensorMapL2promotion, CUtensorMapFloatOOBfill);

CUtensorMap make_map(EncodeFn fn, const void* base, uint64_t inner, uint64_t outer, uint32_t bi, uint32_t bo, CUtensorMapSwizzle sw,
                     CUtensorMapL2promotion pr = CU_TENSOR_MAP_L2_PROMOTION_NONE) {
    CUtensorMap m;
    cuuint64_t dims[2] = {inner, outer};
    cuuint64_t strides[1] = {inner * 2};
    cuuint32_t box[2] = {bi, bo};
    cuuint32_t es[2] = {1, 1};
    fn(&m, CU_TENSOR_MAP_DATA_TYPE_BFLOAT16, 2, (void*)base, dims, strides, box, es, CU_TENSOR_MAP_INTERLEAVE_NONE, sw, pr, CU_TENSOR_MAP_FLOAT_OOB_FILL_NONE);
    return m;
}

}

extern "C" void kernel_launch(void* const* d_in, const int* in_sizes, int n_in, void* d_out, int out_size) {
    (void)in_sizes; (void)n_in; (void)out_size;
    static EncodeFn fn = nullptr;
    static Scratch* scr = nullptr;
    static char* consts = nullptr;
    if (!fn) {
        void* ptr = nullptr; cudaDriverEntryPointQueryResult qr;
        cudaGetDriverEntryPoint("cuTensorMapEncodeTiled", &ptr, cudaEnableDefault, &qr);
        fn = (EncodeFn)ptr;
        cudaGetSymbolAddress((void**)&scr, g_scr);
        cudaGetSymbolAddress((void**)&consts, g_consts);
        cudaFuncSetAttribute(fused_kernel, cudaFuncAttributeMaxDynamicSharedMemorySize, SMEM_BYTES);
    }
    typedef const __nv_bfloat16* bp;
    Params p;
    p.u = (bp)d_in[0]; p.Are = (bp)d_in[1]; p.Aim = (bp)d_in[2]; p.Bre = (bp)d_in[3]; p.Bim = (bp)d_in[4]; p.Cre = (bp)d_in[5]; p.Cim = (bp)d_in[6];
    p.logdt = (bp)d_in[7]; p.Dskip = (bp)d_in[8]; p.wr = (bp)d_in[10]; p.gatew = (bp)d_in[14]; p.wd = (bp)d_in[13];
    p.out = (__nv_bfloat16*)d_out; p.scr = scr; p.consts = consts;
    CUtensorMap mU, mU2;
    {
        cuuint64_t dims[5] = {DM, 8, 2, L_SEQ / 128, 8};
        cuuint64_t strides[4] = {16 * DM * 2, DM * 2, 128 * DM * 2, 2 * DM * 2};
        cuuint32_t box[5] = {16, 4, 2, 4, 8};
        cuuint32_t es[5] = {1, 1, 1, 1, 1};
        fn(&mU, CU_TENSOR_MAP_DATA_TYPE_BFLOAT16, 5, d_in[0], dims, strides, box, es, CU_TENSOR_MAP_INTERLEAVE_NONE, CU_TENSOR_MAP_SWIZZLE_32B,
           CU_TENSOR_MAP_L2_PROMOTION_NONE, CU_TENSOR_MAP_FLOAT_OOB_FILL_NONE);
        box[3] = NL;
        fn(&mU2, CU_TENSOR_MAP_DATA_TYPE_BFLOAT16, 5, d_in[0], dims, strides, box, es, CU_TENSOR_MAP_INTERLEAVE_NONE, CU_TENSOR_MAP_SWIZZLE_32B,
           CU_TENSOR_MAP_L2_PROMOTION_NONE, CU_TENSOR_MAP_FLOAT_OOB_FILL_NONE);
    }
    CUtensorMap mR, mWd;
    {
        cuuint64_t dims[3] = {64, L_SEQ, 9};
        cuuint64_t strides[2] = {DM * 2, 128};
        cuuint32_t box[3] = {64, 8, 9};
        cuuint32_t es[3] = {1, 1, 1};
        fn(&mR, CU_TENSOR_MAP_DATA_TYPE_BFLOAT16, 3, d_in[0], dims, strides, box, es, CU_TENSOR_MAP_INTERLEAVE_NONE, CU_TENSOR_MAP_SWIZZLE_128B,
           CU_TENSOR_MAP_L2_PROMOTION_NONE, CU_TENSOR_MAP_FLOAT_OOB_FILL_NONE);
        dims[0] = 32; dims[1] = FF; dims[2] = 18; strides[1] = 64; box[0] = box[1] = 32;
        fn(&mWd, CU_TENSOR_MAP_DATA_TYPE_BFLOAT16, 3, d_in[13], dims, strides, box, es, CU_TENSOR_MAP_INTERLEAVE_NONE, CU_TENSOR_MAP_SWIZZLE_64B,
           CU_TENSOR_MAP_L2_PROMOTION_L2_128B, CU_TENSOR_MAP_FLOAT_OOB_FILL_NONE);
    }
    WMaps mW;
    mW.m[0] = make_map(fn, d_in[11], FF, DM, 64, 64, CU_TENSOR_MAP_SWIZZLE_128B);
    mW.m[1] = make_map(fn, d_in[12], FF, DM, 64, 64, CU_TENSOR_MAP_SWIZZLE_128B);
    mW.m[2] = make_map(fn, d_in[11], FF, DM, 32, 64, CU_TENSOR_MAP_SWIZZLE_64B, CU_TENSOR_MAP_L2_PROMOTION_L2_128B);
    mW.m[3] = make_map(fn, d_in[12], FF, DM, 32, 64, CU_TENSOR_MAP_SWIZZLE_64B, CU_TENSOR_MAP_L2_PROMOTION_L2_128B);
    fused_kernel<<<NCTA, NTHR, SMEM_BYTES>>>(p, mU, mU2, mR, mW, mWd);
}
```

```cpp
#include <cuda_runtime.h>
#include <cuda_bf16.h>
#include <cuda_fp16.h>
#include <cuda.h>
#include <stdint.h>

#define RDELAY 1300
#define VDELAY 1100
#define HDELAY 2300
#define WDELAY 1800
#define WPER0 870
#define WPER 690
#define DPER 320
#define PDELAY 5500
#define SDELAY 7300
#define KDELAY0 6075
#define KDELAY1 6900
#define KDELAY2 6000
#define KDELAY3 6000
#define KDELAY4 6900
#define GDELAY 600
#define PACE 20
#define SPLITM 3
#define SPLITJ 2
#define AMODE_U 0
#define AMODE_H 3
#define LOOK 0
#define NOUT 2
#define JBAR 4

namespace {

constexpr int L_SEQ = 2048, DM = 576, NST = 128, FF = 4608;
constexpr int NCTA = 132, NFFN = 60, FFN0 = 8, NTHR = 512;
#define NLOW 5
constexpr int NL = NLOW;

struct Scratch {
    unsigned launch; unsigned pad0[31];
    uint32_t sel[32];
    uint32_t zero[72 * 8];
    uint32_t rec[2 * L_SEQ];
    uint4 kx[DM * 4 * 32];
    uint4 part[24 * 30 * 32];
};
__device__ Scratch g_scr;

struct Params {
    const __nv_bfloat16 *Are, *Aim, *Bre, *Bim, *Cre, *Cim, *logdt, *Dskip, *u, *wr, *gatew, *wd;
    __nv_bfloat16* out;
    Scratch* scr;
    const char* consts;
};

__device__ __forceinline__ uint32_t smem_u32(const void* p) { return (uint32_t)__cvta_generic_to_shared(p); }
__device__ __forceinline__ uint32_t pack_bf16(float lo, float hi) { uint32_t r; asm("cvt.rn.bf16x2.f32 %0, %1, %2;" : "=r"(r) : "f"(hi), "f"(lo)); return r; }
__device__ __forceinline__ uint32_t pack_f16(float lo, float hi) { uint32_t r; asm("cvt.rn.f16x2.f32 %0, %1, %2;" : "=r"(r) : "f"(hi), "f"(lo)); return r; }
__device__ __forceinline__ uint32_t prmt(uint32_t a, uint32_t b, uint32_t c) { uint32_t r; asm("prmt.b32 %0, %1, %2, %3;" : "=r"(r) : "r"(a), "r"(b), "r"(c)); return r; }
__device__ __forceinline__ float bf_lo(uint32_t w) { return __uint_as_float(w << 16); }
__device__ __forceinline__ float bf_hi(uint32_t w) { return __uint_as_float(w & 0xffff0000u); }
__device__ __forceinline__ float rbf(float x) { return bf_lo(pack_bf16(x, 0.f)); }
__device__ __forceinline__ uint32_t hmul2(uint32_t a, uint32_t b) { __nv_bfloat162 r = __hmul2_rn(*(__nv_bfloat162*)&a, *(__nv_bfloat162*)&b); return *(uint32_t*)&r; }
__device__ __forceinline__ uint32_t hfma2(uint32_t a, uint32_t b, uint32_t c) { uint32_t r; asm("fma.rn.bf16x2 %0, %1, %2, %3;" : "=r"(r) : "r"(a), "r"(b), "r"(c)); return r; }
__device__ __forceinline__ uint32_t hsub2(uint32_t a, uint32_t b) { __nv_bfloat162 r = __hsub2_rn(*(__nv_bfloat162*)&a, *(__nv_bfloat162*)&b); return *(uint32_t*)&r; }
__device__ __forceinline__ void mma_bf(float (&c)[4], uint32_t a0, uint32_t a1, uint32_t a2, uint32_t a3, uint32_t b0, uint32_t b1) {
    asm("mma.sync.aligned.m16n8k16.row.col.f32.bf16.bf16.f32 {%0,%1,%2,%3}, {%4,%5,%6,%7}, {%8,%9}, {%0,%1,%2,%3};"
        : "+f"(c[0]), "+f"(c[1]), "+f"(c[2]), "+f"(c[3]) : "r"(a0), "r"(a1), "r"(a2), "r"(a3), "r"(b0), "r"(b1));
}
__device__ __forceinline__ void mma_bf0(float (&c)[4], uint32_t a0, uint32_t a1, uint32_t a2, uint32_t a3, uint32_t b0, uint32_t b1) {
    asm("mma.sync.aligned.m16n8k16.row.col.f32.bf16.bf16.f32 {%0,%1,%2,%3}, {%4,%5,%6,%7}, {%8,%9}, {%10,%10,%10,%10};"
        : "=f"(c[0]), "=f"(c[1]), "=f"(c[2]), "=f"(c[3]) : "r"(a0), "r"(a1), "r"(a2), "r"(a3), "r"(b0), "r"(b1), "f"(0.f));
}
__device__ __forceinline__ void mma_bf8(float (&c)[4], uint32_t a0, uint32_t a1, uint32_t b0) {
    asm("mma.sync.aligned.m16n8k8.row.col.f32.bf16.bf16.f32 {%0,%1,%2,%3}, {%4,%5}, {%6}, {%0,%1,%2,%3};"
        : "+f"(c[0]), "+f"(c[1]), "+f"(c[2]), "+f"(c[3]) : "r"(a0), "r"(a1), "r"(b0));
}
__device__ __forceinline__ void mma_f16(float (&c)[4], uint32_t a0, uint32_t a1, uint32_t a2, uint32_t a3, uint32_t b0, uint32_t b1) {
    asm("mma.sync.aligned.m16n8k16.row.col.f32.f16.f16.f32 {%0,%1,%2,%3}, {%4,%5,%6,%7}, {%8,%9}, {%0,%1,%2,%3};"
        : "+f"(c[0]), "+f"(c[1]), "+f"(c[2]), "+f"(c[3]) : "r"(a0), "r"(a1), "r"(a2), "r"(a3), "r"(b0), "r"(b1));
}
__device__ __forceinline__ uint32_t lds32(uint32_t a) { uint32_t v; asm volatile("ld.shared.u32 %0, [%1];" : "=r"(v) : "r"(a)); return v; }
__device__ __forceinline__ uint32_t lds32v(uint32_t a) { uint32_t v; asm volatile("ld.volatile.shared.u32 %0, [%1];" : "=r"(v) : "r"(a)); return v; }
__device__ __forceinline__ uint2 lds64(uint32_t a) { uint2 v; asm volatile("ld.shared.v2.u32 {%0,%1}, [%2];" : "=r"(v.x), "=r"(v.y) : "r"(a)); return v; }
__device__ __forceinline__ uint4 lds128(uint32_t a) { uint4 v; asm volatile("ld.shared.v4.u32 {%0,%1,%2,%3}, [%4];" : "=r"(v.x), "=r"(v.y), "=r"(v.z), "=r"(v.w) : "r"(a)); return v; }
__device__ __forceinline__ void ldsm4(uint32_t (&r)[4], uint32_t a) {
    asm volatile("ldmatrix.sync.aligned.m8n8.x4.shared.b16 {%0,%1,%2,%3}, [%4];" : "=r"(r[0]), "=r"(r[1]), "=r"(r[2]), "=r"(r[3]) : "r"(a));
}
__device__ __forceinline__ void ldsm2(uint32_t (&r)[4], uint32_t a) {
    asm volatile("ldmatrix.sync.aligned.m8n8.x2.shared.b16 {%0,%1}, [%2];" : "=r"(r[0]), "=r"(r[1]) : "r"(a));
}
__device__ __forceinline__ void ldsm4t(uint32_t (&r)[4], uint32_t a) {
    asm volatile("ldmatrix.sync.aligned.m8n8.x4.trans.shared.b16 {%0,%1,%2,%3}, [%4];" : "=r"(r[0]), "=r"(r[1]), "=r"(r[2]), "=r"(r[3]) : "r"(a));
}
__device__ __forceinline__ void sts32(uint32_t a, uint32_t v) { asm volatile("st.shared.u32 [%0], %1;" :: "r"(a), "r"(v) : "memory"); }
__device__ __forceinline__ void sts64(uint32_t a, uint32_t x, uint32_t y) { asm volatile("st.shared.v2.u32 [%0], {%1,%2};" :: "r"(a), "r"(x), "r"(y) : "memory"); }
__device__ __forceinline__ void sts128(uint32_t a, uint32_t x, uint32_t y, uint32_t z, uint32_t w) {
    asm volatile("st.shared.v4.u32 [%0], {%1,%2,%3,%4};" :: "r"(a), "r"(x), "r"(y), "r"(z), "r"(w) : "memory");
}
__device__ __forceinline__ void stsm2(uint32_t a, uint32_t x, uint32_t y) {
    asm volatile("stmatrix.sync.aligned.m8n8.x2.shared.b16 [%0], {%1,%2};" :: "r"(a), "r"(x), "r"(y) : "memory");
}
__device__ __forceinline__ void stsm4t(uint32_t a, uint32_t r0, uint32_t r1, uint32_t r2, uint32_t r3) {
    asm volatile("stmatrix.sync.aligned.m8n8.x4.trans.shared.b16 [%0], {%1,%2,%3,%4};" :: "r"(a), "r"(r0), "r"(r1), "r"(r2), "r"(r3) : "memory");
}
__device__ __forceinline__ void st_async32(uint32_t a, uint32_t x, uint32_t bar) {
    asm volatile("st.async.weak.shared::cluster.mbarrier::complete_tx::bytes.b32 [%0], %1, [%2];" :: "r"(a), "r"(x), "r"(bar) : "memory");
}
__device__ __forceinline__ void st_async128(uint32_t a, uint32_t x, uint32_t y, uint32_t z, uint32_t w, uint32_t bar) {
    asm volatile("st.async.weak.shared::cluster.mbarrier::complete_tx::bytes.v4.b32 [%0], {%1,%2,%3,%4}, [%5];" :: "r"(a), "r"(x), "r"(y), "r"(z), "r"(w), "r"(bar) : "memory");
}
__device__ __forceinline__ void mbar_init(uint32_t b, uint32_t cnt) { asm volatile("mbarrier.init.shared::cta.b64 [%0], %1;" :: "r"(b), "r"(cnt) : "memory"); }
__device__ __forceinline__ void mbar_fence_init() { asm volatile("fence.mbarrier_init.release.cluster;" ::: "memory"); }
__device__ __forceinline__ void mbar_expect(uint32_t b, uint32_t bytes) { asm volatile("mbarrier.arrive.expect_tx.shared::cta.b64 _, [%0], %1;" :: "r"(b), "r"(bytes) : "memory"); }
__device__ __forceinline__ void mbar_arrive(uint32_t b) { asm volatile("mbarrier.arrive.shared::cta.b64 _, [%0];" :: "r"(b) : "memory"); }
__device__ __forceinline__ void mbar_arrive_peer(uint32_t b) { asm volatile("mbarrier.arrive.relaxed.cluster.shared::cluster.b64 _, [%0];" :: "r"(b) : "memory"); }
__device__ __forceinline__ void mbar_wait(uint32_t b) {
    asm volatile("{ .reg .pred p;\nW: mbarrier.try_wait.parity.shared::cta.b64 p, [%0], 0; @!p bra W; }" :: "r"(b) : "memory");
}
__device__ __forceinline__ void tma2d(uint32_t dst, const CUtensorMap* m, int c0, int c1, uint32_t bar) {
    asm volatile("cp.async.bulk.tensor.2d.shared::cluster.global.mbarrier::complete_tx::bytes [%0], [%1, {%3, %4}], [%2];"
                 :: "r"(dst), "l"(m), "r"(bar), "r"(c0), "r"(c1) : "memory");
}
__device__ __forceinline__ void tma3d(uint32_t dst, const CUtensorMap* m, int c0, int c1, int c2, uint32_t bar) {
    asm volatile("cp.async.bulk.tensor.3d.shared::cluster.global.mbarrier::complete_tx::bytes [%0], [%1, {%3, %4, %5}], [%2];"
                 :: "r"(dst), "l"(m), "r"(bar), "r"(c0), "r"(c1), "r"(c2) : "memory");
}
__device__ __forceinline__ void tma5d(uint32_t dst, const CUtensorMap* m, int c0, int c1, int c2, int c3, int c4, uint32_t bar) {
    asm volatile("cp.async.bulk.tensor.5d.shared::cluster.global.mbarrier::complete_tx::bytes [%0], [%1, {%3, %4, %5, %6, %7}], [%2];"
                 :: "r"(dst), "l"(m), "r"(bar), "r"(c0), "r"(c1), "r"(c2), "r"(c3), "r"(c4) : "memory");
}
__device__ __forceinline__ void bulk_load(uint32_t dst, const void* src, uint32_t bytes, uint32_t bar) {
    asm volatile("cp.async.bulk.shared::cluster.global.mbarrier::complete_tx::bytes [%0], [%1], %2, [%3];" :: "r"(dst), "l"(src), "r"(bytes), "r"(bar) : "memory");
}
__device__ __forceinline__ void bulk_load2(uint32_t dst, const void* src, uint32_t bytes, uint32_t bar) {
    asm volatile("cp.async.bulk.shared::cluster.global.mbarrier::complete_tx::bytes.multicast::cluster [%0], [%1], %2, [%3], %4;"
                 :: "r"(dst), "l"(src), "r"(bytes), "r"(bar), "h"((uint16_t)3) : "memory");
}
__device__ __forceinline__ bool elect() { uint32_t d; asm volatile("{ .reg .pred p; elect.sync _|p, 0xffffffff; selp.u32 %0, 1, 0, p; }" : "=r"(d)); return d; }
__device__ __forceinline__ void prefetch_l2(const void* src, uint32_t bytes) { asm volatile("cp.async.bulk.prefetch.L2.global [%0], %1;" :: "l"(src), "r"(bytes) : "memory"); }
__device__ __forceinline__ uint32_t mapa(uint32_t a, uint32_t rank) { uint32_t r; asm("mapa.shared::cluster.u32 %0, %1, %2;" : "=r"(r) : "r"(a), "r"(rank)); return r; }
__device__ __forceinline__ void prefetch_map(const CUtensorMap* m) { asm volatile("prefetch.tensormap [%0];" :: "l"(m) : "memory"); }
__device__ __forceinline__ void bar_sync(int id, int n) { asm volatile("bar.sync %0, %1;" :: "r"(id), "r"(n) : "memory"); }
__device__ __forceinline__ void bar_arrive(int id, int n) { asm volatile("bar.arrive %0, %1;" :: "r"(id), "r"(n) : "memory"); }
__device__ __forceinline__ void cluster_arrive_relaxed() { asm volatile("barrier.cluster.arrive.relaxed.aligned;" ::: "memory"); }
__device__ __forceinline__ void cluster_wait() { asm volatile("barrier.cluster.wait.aligned;" ::: "memory"); }
__device__ __forceinline__ uint32_t ld_rlx32(const void* p) { uint32_t v; asm volatile("ld.relaxed.gpu.global.u32 %0, [%1];" : "=r"(v) : "l"(p) : "memory"); return v; }
__device__ __forceinline__ uint4 ld_rlx128(const void* p) {
    uint4 v; asm volatile("ld.relaxed.gpu.global.v4.u32 {%0,%1,%2,%3}, [%4];" : "=r"(v.x), "=r"(v.y), "=r"(v.z), "=r"(v.w) : "l"(p) : "memory"); return v;
}
__device__ __forceinline__ uint32_t ld_acq32(const void* p) { uint32_t v; asm volatile("ld.acquire.gpu.global.u32 %0, [%1];" : "=r"(v) : "l"(p) : "memory"); return v; }
__device__ __forceinline__ void red_bf2(void* p, uint32_t v) { asm volatile("red.relaxed.gpu.global.add.noftz.bf16x2 [%0], %1;" :: "l"(p), "r"(v) : "memory"); }
__device__ __forceinline__ uint32_t take_ticket(unsigned* p) { uint32_t v; asm volatile("atom.relaxed.gpu.global.add.u32 %0, [%1], 1;" : "=r"(v) : "l"(p) : "memory"); return v; }
__device__ __forceinline__ void st_rlx32(void* p, uint32_t v) { asm volatile("st.relaxed.gpu.global.u32 [%0], %1;" :: "l"(p), "r"(v) : "memory"); }
__device__ __forceinline__ void st_pkt(void* p, uint32_t x, uint32_t y, uint32_t z, uint32_t w) {
    asm volatile("{ .reg .b64 lo, hi; .reg .b128 v; mov.b64 lo, {%1, %2}; mov.b64 hi, {%3, %4}; mov.b128 v, {lo, hi}; st.relaxed.gpu.global.b128 [%0], v; }"
                 :: "l"(p), "r"(x), "r"(y), "r"(z), "r"(w) : "memory");
}
__device__ __forceinline__ uint4 ld_pkt(const void* p) {
    uint4 r;
    asm volatile("{ .reg .b64 lo, hi; .reg .b128 v; ld.relaxed.gpu.global.b128 v, [%4]; mov.b128 {lo, hi}, v; mov.b64 {%0, %1}, lo; mov.b64 {%2, %3}, hi; }"
                 : "=r"(r.x), "=r"(r.y), "=r"(r.z), "=r"(r.w) : "l"(p) : "memory");
    return r;
}
__device__ __forceinline__ uint32_t tag_of(uint32_t ticket) { return ticket / NCTA % 3u + 1u; }
__device__ __forceinline__ uint32_t ldg32(const void* p) { uint32_t v; asm volatile("ld.global.nc.u32 %0, [%1];" : "=r"(v) : "l"(p)); return v; }
__device__ __forceinline__ uint32_t ldg16(const void* p) { uint32_t v; asm volatile("ld.global.nc.u16 %0, [%1];" : "=r"(v) : "l"(p)); return v; }
__device__ __forceinline__ int warp_id() { return __shfl_sync(0xffffffffu, threadIdx.x >> 5, 0); }
__device__ __forceinline__ int lane_id() {
    const int l = __shfl_sync(0xffffffffu, threadIdx.x & 31, threadIdx.x);
    __builtin_assume(l >= 0 && l < 32);
    return l;
}
__device__ __forceinline__ uint32_t clk() { uint32_t t; asm volatile("mov.u32 %0, %clock;" : "=r"(t) :: "memory"); return t; }
__device__ __forceinline__ void spin_until(uint32_t t0, uint32_t d) { while (clk() - t0 < d) {} }
template <int NS>
__device__ __forceinline__ void sleep_until(uint32_t t) {
    asm volatile("{ .reg .pred p; .reg .s32 c;\nW: mov.u32 c, %clock; sub.s32 c, c, %0; setp.lt.s32 p, c, 0; @p nanosleep.u32 %1; @p bra W; }" :: "r"(t), "n"(NS) : "memory");
}
__device__ __forceinline__ float sigmoidf_(float x) { return __fdividef(1.0f, 1.0f + __expf(-x)); }
__device__ __forceinline__ int key_row(uint32_t key) { return 2047 - (int)(key & 2047u); }
__device__ __forceinline__ uint32_t key_thr(uint32_t key) { return __byte_perm(key & 2047u, key << 3, 0x7610); }
__device__ __forceinline__ float key_val(uint32_t key) {
    const uint32_t o = (key << 3) & 0xffff0000u; return __uint_as_float((o & 0x80000000u) ? (o & 0x7fffffffu) : (~o & 0xffff0000u));
}
#define RARE(x) __builtin_expect(!!(x), 0)
#define POLL_GUARD(it) (void)(it)

constexpr int UT_PL = 2240, UT_STRIDE = 4544;
constexpr int KT_P = 0, KT_P4 = 544 * 4, KT_P8 = KT_P4 + 172 * 4, KT_BYTES = KT_P8 + 140 * 4;
constexpr int KG_ROW = 272, KG_STAGE = 33 * KG_ROW;
constexpr int OUT_HALF = 2368, OUT_STAGE = 2 * OUT_HALF;
constexpr int SC_UTILE = 0;
constexpr int SC_UT = 32768;
constexpr int SC_STG = SC_UT + 8 * UT_STRIDE;
constexpr int SC_KT = SC_STG + 8 * KG_STAGE;
constexpr int SC_OUT = SC_KT + 8 * KT_BYTES;
constexpr int SC_CT = SC_OUT + 8 * OUT_STAGE;
constexpr int SC_BAR = SC_CT + 4096;
constexpr int SB_UT = SC_BAR + 32, SB_OUT = SC_BAR + 64, SC_KEY = SC_BAR + 128, SC_TAG = SC_BAR + 160;
constexpr int SC_END = SC_BAR + 256;
static_assert(SC_STG % 128 == 0 && SC_OUT % 128 == 0 && SC_KT % 16 == 0, "align");
constexpr int PIECE_P = 24576, PIECE_H = 16384, DPIECE = 18432;
constexpr int SF_LIST = 9 * PIECE_P, SF_WR = SF_LIST + 4096;
constexpr int SF_XS = SF_LIST + 384;
constexpr int SF_BAR = SF_XS + 9344;
constexpr int FB_W = SF_BAR, FB_D = FB_W + 72, FB_GU = FB_D + 40, FB_FREE = FB_GU + 8, FB_SEL = FB_FREE + 16, FB_KG = FB_SEL + 8, FB_TK = FB_KG + 8, FB_UT = FB_TK + 8,
              FB_X = FB_UT + 8, FB_WR = FB_X + 8, FB_PEER = FB_WR + 8, FB_R = FB_PEER + 16, FB_RAW = FB_R + 48;
constexpr int SF_MAX = FB_RAW + 8, SF_CNT = SF_MAX + 64, SF_TK = SF_CNT + 4, SF_CLK = SF_CNT + 8, SF_TN = SF_CNT + 16, SF_SEL = SF_CNT + 32;
constexpr int SF_END = SF_SEL + 32;
constexpr int SP_R = 83 * 1024, SP_STG = SF_LIST - 12 * KG_STAGE, SP_H = DPIECE, SP_RED = 5 * PIECE_P;
constexpr int UH_PL = 128 + 128 * NL + 64, UH_STRIDE = 2 * UH_PL - 64, UH_HI = 8 * UH_STRIDE + 32, KH_BYTES = KT_P4 + 176 * 4, OH_STRIDE = 512 * ((NL + 1) / 2) + 64;
constexpr int SH_UT = 9 * PIECE_H, SH_R = SH_UT, SH_R5 = 4 * PIECE_H, SH_STG = SH_UT - 8 * KG_STAGE, SH_H = SH_UT + 16 * UH_STRIDE + 128, SH_OUT = SH_H + 2560;
constexpr int SH_CT = SH_R + 5 * 9216, SH_RAW = SF_LIST - NL * 4096, SH_KT = SF_LIST - 8 * KH_BYTES;
constexpr int SM_TIM = SF_END;
constexpr int SMEM_BYTES = SF_END + 272;
static_assert(SP_R + 3 * 9216 <= SP_STG && SP_R >= 3 * PIECE_P && SP_STG >= 4 * PIECE_P && SH_R5 + 9216 <= SH_STG && SH_OUT + 8 * OH_STRIDE <= SH_CT && (SH_KT - SH_OUT) % 64 == 0 && KH_BYTES % 128 == 64 && SH_CT + 3584 <= SH_RAW &&
              SH_CT + 3584 <= SH_KT && SF_MAX % 16 == 0 && SMEM_BYTES <= 232448 && SC_END <= SF_END, "smem");

struct cplx { float re, im; };
struct h2c { uint32_t re, im; };
__device__ __forceinline__ cplx csq(cplx a) {
    cplx r; r.re = a.re * a.re - a.im * a.im;
    asm("{ .reg .f32 t; mul.f32 t, %1, %2; mul.f32 %0, t, 0f40000000; }" : "=f"(r.im) : "f"(a.re), "f"(a.im));
    return r;
}
__device__ __forceinline__ float ex2(float x) { float m; asm("ex2.approx.ftz.f32 %0, %1;" : "=f"(m) : "f"(x)); return m; }
__device__ __forceinline__ cplx cexp2(float x, float y) {
    const float m = ex2(x);
    cplx o; o.re = m * __cosf(y); o.im = m * __sinf(y); return o;
}
__device__ __forceinline__ h2c hpack(cplx a, cplx b) { h2c r; r.re = pack_f16(a.re, b.re); r.im = pack_f16(a.im, b.im); return r; }
__device__ __forceinline__ h2c hmulc(h2c a, h2c m) {
    h2c r;
    asm("{ .reg .b32 s, t; mul.f16x2 s, %3, %5; mul.f16x2 t, %3, %4; neg.f16x2 s, s; fma.rn.f16x2 %0, %2, %4, s; fma.rn.f16x2 %1, %2, %5, t; }"
        : "=&r"(r.re), "=r"(r.im) : "r"(a.re), "r"(a.im), "r"(m.re), "r"(m.im));
    return r;
}
__device__ __forceinline__ h2c hmulj(h2c a, h2c m) {
    h2c r;
    asm("{ .reg .b32 s, t; mul.f16x2 s, %3, %5; mul.f16x2 t, %2, %5; neg.f16x2 t, t; fma.rn.f16x2 %0, %2, %4, s; fma.rn.f16x2 %1, %3, %4, t; }"
        : "=&r"(r.re), "=r"(r.im) : "r"(a.re), "r"(a.im), "r"(m.re), "r"(m.im));
    return r;
}

struct KParams { uint32_t v[6], logdt, dskip; };
__device__ __forceinline__ KParams kload(const Params& p, int ch, int half) {
    KParams k;
    const int o = ch * NST + 64 * half + 2 * (threadIdx.x & 31);
    const __nv_bfloat16* a[8] = {p.Are + o, p.Aim + o, p.Bre + o, p.Bim + o, p.Cre + o, p.Cim + o, p.logdt + ch, p.Dskip + ch};
#pragma unroll
    for (int i = 0; i < 6; i++) k.v[i] = ldg32(a[i]);
    k.logdt = ldg16(a[6]);
    k.dskip = ldg16(a[7]);
    return k;
}

__device__ __forceinline__ void kgen(int lane, const KParams& k, uint32_t stage, float (&kv)[21], float& fin, uint32_t sb) {
    const int mi = lane >> 3, r8 = lane & 7;
    const uint32_t (&v)[6] = k.v;
    const uint32_t w2 = stage + (lane & 15) * 16, w1 = stage + lane * 4;
    auto put = [&](int row, h2c x) { stsm2(w2 + row * KG_ROW, x.re, x.im); };
    auto keep = [&](int row, h2c x) { sts32(w1 + row * KG_ROW, x.re); sts32(w1 + row * KG_ROW + 128, x.im); };
    sts32(w1, 0x3c003c00u); sts32(w1 + 128, 0u);
    const float dt = rbf(ex2(bf_lo(k.logdt) * 1.4426950408889634f));
    const float dl = dt * 1.4426950408889634f;
    const float xa = bf_lo(v[0]) * dl, xb = bf_hi(v[0]) * dl, ya = bf_lo(v[1]) * dt, yb = bf_hi(v[1]) * dt;
    cplx a = cexp2(xa, ya), b = cexp2(xb, yb), c = cexp2(64.f * xa, 64.f * ya), d = cexp2(64.f * xb, 64.f * yb);
    cplx Wa, Wb;
    Wa.re = bf_lo(v[4]) * bf_lo(v[2]) - bf_lo(v[5]) * bf_lo(v[3]); Wa.im = bf_lo(v[4]) * bf_lo(v[3]) + bf_lo(v[5]) * bf_lo(v[2]);
    Wb.re = bf_hi(v[4]) * bf_hi(v[2]) - bf_hi(v[5]) * bf_hi(v[3]); Wb.im = bf_hi(v[4]) * bf_hi(v[3]) + bf_hi(v[5]) * bf_hi(v[2]);
    const float mx = fmaxf(fmaxf(fabsf(Wa.re), fabsf(Wa.im)), fmaxf(fabsf(Wb.re), fabsf(Wb.im)));
    const uint32_t ex = max(__reduce_max_sync(0xffffffffu, __float_as_uint(mx)) >> 23, 10u);
    const float sc = __uint_as_float((263u - ex) << 23);
    fin = dt * __uint_as_float((ex - 9u) << 23);
    Wa.re *= sc; Wa.im *= sc; Wb.re *= sc; Wb.im *= sc;
    kv[16] = (float)__reduce_add_sync(0xffffffffu, __float2int_rn((Wa.re + Wb.re) * 32768.f)) * (1.f / 32768.f);
    h2c c1;
    {
        cplx p, q;
        p.re = Wa.re * a.re - Wa.im * a.im; p.im = -(Wa.re * a.im) - Wa.im * a.re; q.re = Wb.re * b.re - Wb.im * b.im; q.im = -(Wb.re * b.im) - Wb.im * b.re;
        c1 = hpack(p, q);
    }
    const h2c z1 = hpack(a, b); a = csq(a); b = csq(b);
    const h2c z64 = hpack(c, d); c = csq(c); d = csq(d);
    const h2c z2 = hpack(a, b); a = csq(a); b = csq(b);
    const h2c z128 = hpack(c, d); c = csq(c); d = csq(d);
    const h2c z4 = hpack(a, b); a = csq(a); b = csq(b);
    const h2c z256 = hpack(c, d); c = csq(c); d = csq(d);
    const h2c z8 = hpack(a, b); a = csq(a); b = csq(b);
    const h2c z512 = hpack(c, d);
    const h2c z16 = hpack(a, b); a = csq(a); b = csq(b);
    const h2c z32 = hpack(a, b);
    keep(32, z64);
    const h2c c2 = hmulj(c1, z1), c3 = hmulj(c1, z2), c4 = hmulj(c2, z2), c6 = hmulj(c2, z4), c8 = hmulj(c4, z4);
    keep(8, c1); keep(9, c2); keep(10, c3); keep(11, c4); put(12, hmulj(c1, z4)); keep(13, c6); put(14, hmulj(c3, z4)); keep(15, c8);
    const h2c e260 = hmulj(c4, z256), e264 = hmulj(c8, z256), e776 = hmulj(e264, z512), e840 = hmulj(e776, z64);
    put(16, hmulj(c2, z256)); put(17, hmulj(c4, z512)); keep(18, e260); put(19, hmulj(c8, z512)); put(20, hmulj(c6, z256)); put(21, hmulj(e260, z512)); keep(22, e264); keep(23, e776);
    const h2c z24 = hmulc(z8, z16);
    keep(1, z8); keep(2, z16); keep(3, z24); keep(4, z32); put(5, hmulc(z8, z32)); put(6, hmulc(z16, z32)); put(7, hmulc(z24, z32));
    const h2c d0 = hmulj(e840, z128), d1 = hmulj(e840, z256), d3 = hmulj(e840, z512), d2 = hmulj(d0, z256);
    keep(24, d0); keep(25, d1); keep(27, d3); keep(26, d2); put(28, hmulj(d0, z512)); put(29, hmulj(d1, z512)); put(31, hmulj(d3, z512)); put(30, hmulj(d2, z512));
    __syncwarp();
    cluster_wait();
    const uint32_t ra = stage + ((mi & 1) ? 32 : r8) * KG_ROW + (mi >> 1) * 128, rb = stage + (8 + r8) * KG_ROW + (mi & 1) * 128 + (mi >> 1) * 16;
    float acc[5][4];
#pragma unroll
    for (int i = 0; i < 5; i++) acc[i][0] = acc[i][1] = acc[i][2] = acc[i][3] = 0.f;
#pragma unroll
    for (int s = 0; s < 4; s++) {
        uint32_t A[2][4], B[3][4];
        ldsm4(A[0], ra + 32 * s); ldsm4(A[1], ra + 32 * s + 16);
        ldsm4(B[0], rb + 32 * s); ldsm4(B[1], rb + 32 * s + 8 * KG_ROW); ldsm4(B[2], rb + 32 * s + 16 * KG_ROW);
#pragma unroll
        for (int e = 0; e < 2; e++) {
            const h2c p0 = {A[e][0], A[e][2]}, m = {A[e][1], A[e][3]};
            const h2c p1 = hmulc(p0, m), p2 = hmulc(p1, m), p3 = hmulc(p2, m);
            mma_f16(acc[1], p1.re, p2.re, p1.im, p2.im, B[0][2 * e], B[0][2 * e + 1]);
            mma_f16(acc[3], p1.re, p2.re, p1.im, p2.im, B[1][2 * e], B[1][2 * e + 1]);
            mma_f16(acc[4], p1.re, p2.re, p1.im, p2.im, B[2][2 * e], B[2][2 * e + 1]);
            mma_f16(acc[0], p0.re, p3.re, p0.im, p3.im, B[0][2 * e], B[0][2 * e + 1]);
            mma_f16(acc[2], p0.re, p3.re, p0.im, p3.im, B[1][2 * e], B[1][2 * e + 1]);
        }
    }
#pragma unroll
    for (int q = 0; q < 4; q++) {
        const int i = (q == 1 || q == 2), h = 2 * (q >> 1);
        kv[2 * q] = acc[i][h]; kv[2 * q + 1] = acc[i][h + 1]; kv[8 + q] = acc[2 + i][h]; kv[12 + q] = acc[2 + i][h + 1]; kv[17 + q] = acc[4][2 * (q & 1) + (q >> 1)];
    }
}
__device__ __forceinline__ void ksend(int lane, const float (&kv)[21], float fin, uint32_t mine, bool second) {
    const uint32_t lo = lane * 16;
    auto send = [&](int i, int k) { sts128(mine + lo + 512 * i, __float_as_uint(kv[k] * fin), __float_as_uint(kv[k + 1] * fin), __float_as_uint(kv[k + 2] * fin), __float_as_uint(kv[k + 3] * fin)); };
    __syncwarp();
    if (second) send(0, 17);
    else { send(0, 0); send(1, 4); send(2, 8); send(3, 12); sts32(mine + 2048, __float_as_uint(kv[16] * fin)); }
}
__device__ __forceinline__ void krecv(int lane, float (&kv)[21], float fin, uint32_t other, int i, int k) {
    const uint4 x = lds128(other + lane * 16 + 512 * i);
    kv[k] = kv[k] * fin + __uint_as_float(x.x); kv[k + 1] = kv[k + 1] * fin + __uint_as_float(x.y); kv[k + 2] = kv[k + 2] * fin + __uint_as_float(x.z); kv[k + 3] = kv[k + 3] * fin + __uint_as_float(x.w);
}

__device__ __forceinline__ void kpack(int lane, const float (&kv)[21], uint4 (&x)[4]) {
    const uint32_t w512 = pack_bf16(__shfl_sync(0xffffffffu, kv[11], 31), 0.f);
    const float up = __shfl_up_sync(0xffffffffu, kv[15], 2), k512 = bf_lo(w512);
    x[0] = make_uint4(pack_bf16(kv[1], kv[3]), pack_bf16(kv[5], kv[7]), pack_bf16(kv[8], kv[9]), w512);
    x[1] = make_uint4(pack_bf16(kv[10], lane < 30 ? kv[11] : lane == 31 ? 0.f : kv[11] - k512), pack_bf16(kv[0], kv[2]), pack_bf16(kv[4], kv[6]), 0);
    x[2] = make_uint4(pack_bf16(kv[12], kv[13]), pack_bf16(kv[14], kv[15]), pack_bf16((lane & 2) ? up : lane == 29 ? k512 : 0.f, kv[16]), 0);
}
__device__ __forceinline__ void kstore(int lane, const uint4 (&x)[4], uint32_t kt, uint32_t ct) {
    const uint4 c = lds128(ct + lane * 16 + 2560), d = lds128(ct + lane * 16 + 3072);
    const uint32_t h[4] = {x[0].x, x[0].y, x[0].z, x[1].x}, l[2] = {x[1].y, x[1].z};
    uint32_t carry = x[2].z;
    if (lane == 0) sts32(kt + KT_P + 15 * 4, carry >> 16);
#pragma unroll
    for (int i = 0; i < 4; i++) {
        const uint32_t sh = __shfl_sync(0xffffffffu, h[i], lane + 31), pv = prmt(sh, carry, d.x);
        carry = sh;
#pragma unroll
        for (int e = 0; e < 2; e++) {
            const uint32_t a = kt + KT_P + (128 * i + 64 * e + 16) * 4 + lane * 8;
            if (i < 2) sts64(a, __byte_perm(l[i], pv, 0x5410 + 0x2222 * e), __byte_perm(h[i], l[i], 0x5410 + 0x2222 * e));
            else sts64(a, prmt(h[i], pv, e ? c.z : c.x), prmt(h[i], pv, e ? c.w : c.y));
        }
    }
    const uint32_t a4 = kt + d.y;
    sts32(a4, __byte_perm(x[2].x, x[2].z, 0x5410)); sts32(a4 + 64, __byte_perm(x[2].x, 0, 0x1032));
    sts32(a4 + 128, __byte_perm(x[2].y, x[2].x, 0x7610)); sts32(a4 + 192, __byte_perm(x[2].y, 0, 0x1032));
    sts32(kt + d.z, prmt(x[2].y, x[0].w, d.w));
}
__device__ __forceinline__ uint4 kwords8(int lane, const float (&kv)[21]) {
    const float up = __shfl_up_sync(0xffffffffu, kv[20], 1);
    return make_uint4(pack_bf16(kv[17], (lane & 3) ? up : 0.f), pack_bf16(kv[18], kv[17]), pack_bf16(kv[19], kv[18]), pack_bf16(kv[20], kv[19]));
}

constexpr uint32_t band(int e, int c, int h) { return (((unsigned)(e - c + h) <= 2u * h) ? 0x3f80u : 0u) | (((unsigned)(e + 1 - c + h) <= 2u * h) ? 0x3f800000u : 0u); }

struct alignas(128) Consts { uint32_t a[7][32][4]; };
constexpr Consts conv_consts(int pl) {
    Consts c = {};
    for (int lane = 0; lane < 32; lane++) {
        const int g = lane >> 2, t = lane & 3, mi = lane >> 3, r8 = lane & 7, d0 = g - 2 * t, pg = (g >> 1) + 4 * (g & 1);
        const uint32_t sa = (lane & 1) ? 0x5410 : 0x5454, sb = (lane & 1) ? 0x1010 : 0x5410, a4 = KT_P4 + (13 + 2 * g + (t & 1) + 64 * (t >> 1)) * 4;
        const uint32_t v[28] = {
            band(4 * t, 4 + g, 4), band(4 * t, 4 + g, 3), band(4 * t + 2, 4 + g, 4), band(4 * t + 2, 4 + g, 3),
            (uint32_t)(pg * 16 + (t == 0 ? pl - 8 : t == 3 ? pl : 8 * (t - 1))), (uint32_t)(pg * 16 + (t == 0 ? -8 : t == 3 ? 0 : pl - 16 + 8 * (t - 1))),
            (uint32_t)((mi & 1) * pl + (mi >> 1) * 128 + r8 * 16), (uint32_t)(KT_P + (15 + d0) * 4),
            (((unsigned)(d0 - 3) < 2u) ? 0xffffu : 0u) | (((unsigned)(d0 - 4) < 2u) ? 0xffff0000u : 0u),
            (((unsigned)(d0 + 5) < 2u) ? 0xffffu : 0u) | (((unsigned)(d0 + 4) < 2u) ? 0xffff0000u : 0u), (uint32_t)(KT_P4 + (3 + g - t) * 16), (uint32_t)(pl - 16 + lane * 16),
            band(2 * t, 6 + g, 2), band(2 * t, 2 + g, 1), band(2 * t + 8, 6 + g, 2), band(2 * t + 8, 2 + g, 1),
            (uint32_t)(pg * 16 + (t == 3 ? pl : 4 + 4 * t)), (uint32_t)(pg * 16 + (t == 3 ? 16 : pl + 4 + 4 * t)), 0, 0,
            sa, sb, sa + 0x2222, sb + 0x2222, lane ? 0x3210u : 0x1076u, a4, t >= 2 ? a4 + 256 : KT_P4 + 12 * 4, t >= 2 ? 0x3277u : 0x7754u};
        for (int i = 0; i < 28; i++) c.a[i >> 2][lane][i & 3] = v[i];
    }
    return c;
}
__device__ const Consts g_consts[2] = {conv_consts(UT_PL), conv_consts(UH_PL)};

__device__ __forceinline__ void conv_windows(int lane, uint32_t sb, int warp, uint32_t (&q)[8][4]) {
    const uint32_t ut = sb + SC_UT + warp * UT_STRIDE + 128, ct = sb + SC_CT + lane * 16;
    const uint2 c1 = lds64(ct + 512);
    const uint4 c0 = lds128(ct);
    const uint32_t w0 = c0.x, w1 = c0.y, w2 = c0.z, w3 = c0.w, a0 = ut + c1.x, a1 = ut + c1.y;
#pragma unroll
    for (int j = 0; j < 8; j++) {
        const uint2 x = lds64(a0 + 128 * j - 16), y = lds64(a1 + 128 * j), z = lds64(a0 + 128 * j);
        float X[4], Y[4], Z[4];
        mma_bf0(X, w0, w1, w2, w3, x.x, x.y); mma_bf0(Y, w0, w1, w2, w3, y.x, y.y); mma_bf0(Z, w0, w1, w2, w3, z.x, z.y);
        q[j][0] = pack_bf16(Y[2], Y[3]); q[j][1] = pack_bf16(Z[2], Z[3]); q[j][2] = pack_bf16(X[0], X[1]); q[j][3] = pack_bf16(Y[0], Y[1]);
    }
}
template <int N>
__device__ __forceinline__ void kissue(int lane, const Params& p, int ch, uint4 (&x)[4]) {
    const uint4* src = p.scr->kx + ch * 128 + lane;
#pragma unroll
    for (int i = 0; i < N; i++) x[i] = ld_pkt(src + 32 * i);
}
template <int N>
__device__ __forceinline__ void kfetch(int lane, const Params& p, int ch, uint32_t tag, uint4 (&x)[4]) {
    tag <<= 16;
    for (int it = 0; !__all_sync(0xffffffffu, ((x[0].w ^ tag) | (x[1].w ^ tag) | (x[2].w ^ tag) | (x[N - 1].w ^ tag)) < 0x10000u);) {
        kissue<N>(lane, p, ch, x);
        POLL_GUARD(it);
    }
}
__device__ __forceinline__ void kpublish(int lane, const Params& p, int ch, uint32_t tag, uint4 (&x)[4]) {
    uint4* const dst = p.scr->kx + ch * 128 + lane;
#pragma unroll
    for (int i = 0; i < 3; i++) { x[i].w |= tag << 16; st_pkt(dst + 32 * i, x[i].x, x[i].y, x[i].z, x[i].w); }
}

template <int LO, int HI>
__device__ __forceinline__ void conv_core(float (&acc)[16][4], uint32_t sb, int warp, uint32_t kt, uint32_t ut, uint32_t ct, uint32_t out) {
    const uint32_t oz = blockIdx.y;
    const uint2 c1 = lds64(ct + 520);
    uint4 c2;
    {
        uint32_t a[4][4], b[8][4];
        uint32_t k1 = kt + c1.y, u1 = ut + c1.x;
        constexpr int AM = LO ? AMODE_U : AMODE_H;
        auto lda = [&](int j1, bool first) {
            a[j1][2] = (AM & 1) && !first ? a[j1][1] + oz : lds32v(k1 + 512 * j1 - 32);
            a[j1][0] = lds32(k1 + 512 * j1); a[j1][1] = lds32(k1 + 512 * j1 + 32);
            a[j1][3] = (AM & 2) ? a[j1][0] + oz : lds32v(k1 + 512 * j1);
        };
        auto ldb = [&](int m2) { if (2 * m2 + 1 < HI) ldsm4(b[m2], u1 + 256 * m2); else ldsm2(b[m2], u1 + 256 * m2); };
        lda(0, true);
#pragma unroll
        for (int m2 = LO / 2; m2 < (HI + 1) / 2; m2++) ldb(m2);
#pragma unroll
        for (int i = 0; i < (LO ? 8 : 16); i++) acc[i][0] = acc[i][1] = acc[i][2] = acc[i][3] = 0.f;
        auto pass = [&](bool last) {
            k1 += 64; u1 -= 16;
            lda(3, false);
#pragma unroll
            for (int m = 0; m < HI; m++) {
                if (m >= LO) mma_bf(acc[m], a[0][0], a[0][1], a[0][2], a[0][3], b[m >> 1][2 * (m & 1)], b[m >> 1][2 * (m & 1) + 1]);
                if (((m & 1) || m == HI - 1) && (m + 3 >= LO || last)) ldb(m >> 1);
            }
            lda(2, false); lda(1, false); lda(0, false);
#pragma unroll
            for (int j1 = 3; j1 > 0; j1--)
#pragma unroll
                for (int m = last; m + j1 < HI; m++)
                    if (m + j1 >= LO) mma_bf(acc[m + j1 + (!LO && j1 >= SPLITJ && m + j1 >= SPLITM ? 8 : 0)], a[j1][0], a[j1][1], a[j1][2], a[j1][3], b[m >> 1][2 * (m & 1)], b[m >> 1][2 * (m & 1) + 1]);
        };
        if (AM & 1) for (int j1 = 1; j1 < 4; j1++) a[j1][1] = lds32(k1 + 512 * j1 + 32);
#pragma unroll
        for (int j0 = 0; j0 < 8; j0++) pass(j0 == 7);
        if (!LO) {
#pragma unroll
            for (int i = SPLITM; i < HI; i++) { acc[i][0] += acc[i + 8][0]; acc[i][1] += acc[i + 8][1]; acc[i][2] += acc[i + 8][2]; acc[i][3] += acc[i + 8][3]; }
        }
        c2 = lds128(ct + 1024);
#pragma unroll
        for (int m = LO ? LO : 1; m < HI; m++) mma_bf(acc[m], a[0][0], a[0][1], a[0][2], a[0][3], b[m >> 1][2 * (m & 1)], b[m >> 1][2 * (m & 1) + 1]);
        if (HI > 8) {
            const uint32_t kv = __byte_perm(lds32(kt + KT_P4 + 140 * 4), 0, 0x1010), e0 = kv & c2.x, e1 = kv & c2.y;
            const uint32_t e3 = e0 + oz, e4 = e1 + oz, z2 = oz + oz;
            uint32_t f[2][4];
            ldsm4(f[0], ut + c2.w); ldsm4(f[1], ut + c2.w + 512);
#pragma unroll
            for (int m = 1; m < 9; m++) mma_bf(acc[m + 7], e0, e1, oz, e3, b[m >> 1][2 * (m & 1)], b[m >> 1][2 * (m & 1) + 1]);
#pragma unroll
            for (int m = 0; m < 8; m++) mma_bf8(acc[m + 8], e4, z2, f[m >> 2][m & 3]);
        }
    }
    if (LO) { }
    uint32_t kb[5][4];
#pragma unroll
    for (int l = 0; l < 5; l++) if (l + 3 < HI) { const uint4 x = lds128(kt + c2.z + 128 * l); kb[l][0] = x.x; kb[l][1] = x.y; kb[l][2] = x.z; kb[l][3] = x.w; }
    const uint4 c3 = lds128(ct + 1536);
    const uint2 c4 = lds64(ct + 2048), c5 = LO ? lds64(ct + 3584) : c4;
    const uint32_t w0 = c3.x, w1 = c3.y, w2 = c3.z, w3 = c3.w, a0 = ut + c4.x, a1 = ut + c4.y;
    auto emit = [&](int q) {
        const uint32_t y0 = pack_bf16(acc[2 * q][0], acc[2 * q][1]), y1 = pack_bf16(acc[2 * q][2], acc[2 * q][3]);
        const uint32_t y2 = pack_bf16(acc[2 * q + 1][0], acc[2 * q + 1][1]), y3 = pack_bf16(acc[2 * q + 1][2], acc[2 * q + 1][3]);
        if (LO) st_async128(c5.x + out + q * OUT_STAGE, y0, y1, y2, y3, c5.y + 8 * q);
        else stsm4t(out + 512 * q, y0, y1, y2, y3);
    };
    uint32_t x[12][4];
    auto load = [&](int j) { x[j][0] = lds32(a0 + 128 * j - 16); x[j][1] = lds32(a1 + 128 * j - 16); x[j][2] = lds32(a0 + 128 * j); x[j][3] = lds32(a1 + 128 * j); };
    {
        float Z[4] = {0.f, 0.f, 0.f, 0.f};
        mma_bf8(Z, w2, w3, lds32(a1 - 128));
        const uint32_t z5 = pack_bf16(Z[0], Z[1]);
#pragma unroll
        for (int l = 0; l < 5; l++) if (3 + l >= LO && 3 + l < HI) mma_bf8(acc[3 + l], oz * 3, z5, kb[l][0]);
    }
    if (HI > 4) load(0);
    if (HI > 5) load(1);
    if (!LO) { __syncwarp(); emit(0); emit(1); }
    uint32_t W[12][8];
#pragma unroll
    for (int j = 0; j + 4 < HI; j++) {
        if (LO) {
            if (j == JBAR) bar_sync(2 + (warp & 3), 64);
            if (j + 2 < 11) load(j + 2);
            if (j == 10) load(11);
        }
        float X[4], Y[4], Z[4];
        mma_bf0(X, w0, w1, w2, w3, x[j][0], x[j][1]); mma_bf0(Y, w0, w1, w2, w3, x[j][1] + oz, x[j][2] + oz); mma_bf0(Z, w0, w1, w2, w3, x[j][2], x[j][3]);
        W[j][0] = pack_bf16(Y[0], Y[1]); W[j][1] = pack_bf16(Z[0], Z[1]); W[j][2] = pack_bf16(Y[2], Y[3]); W[j][3] = pack_bf16(Z[2], Z[3]);
        W[j][4] = pack_bf16(X[0], X[1]); W[j][5] = W[j][0] + oz; W[j][6] = pack_bf16(X[2], X[3]); W[j][7] = W[j][2] + oz;
#pragma unroll
        for (int i = 0; i <= j; i++)
#pragma unroll
            for (int h = 0; h < 2; h++)
#pragma unroll
                for (int l = 0; l < 5; l++) {
                    const int m = i + 4 + l, when = max(i, (m & ~1) - 4 - LOOK + (LOOK < 4 ? (i & 1) : 0));
                    if (when == j && m < HI && m >= LO) mma_bf(acc[m], W[i][4 * h], W[i][4 * h + 1], W[i][4 * h + 2], W[i][4 * h + 3], kb[l][2 * h], kb[l][2 * h + 1]);
                }
        if (((j & 1) || j + 5 == HI) && j + 4 >= LO) emit(2 + (j >> 1));
    }
}

__device__ __forceinline__ void conv_warp(int lane, uint32_t sb, int warp, const uint32_t (&q)[8][4], uint4 k8) {
    const uint32_t kt = sb + SC_KT + warp * KT_BYTES;
    float acc[16][4];
    const uint32_t a8 = kt + KT_P8 + (6 + 32 * (lane & 3) + (lane >> 2)) * 4;
    sts32(a8, k8.x); sts32(a8 + 32, k8.y); sts32(a8 + 64, k8.z); sts32(a8 + 96, k8.w);
    __syncwarp();
#pragma unroll
    for (int l = 0; l < 8; l++) {
        const uint2 kb = lds64(kt + KT_P8 + (3 + 8 * l + (lane >> 2) - (lane & 3)) * 8);
#pragma unroll
        for (int j = 0; j < 8 - l; j++) {
            if (l == 0) mma_bf0(acc[8 + j], q[j][0], q[j][1], q[j][2], q[j][3], kb.x, kb.y);
            else mma_bf(acc[8 + j + l], q[j][0], q[j][1], q[j][2], q[j][3], kb.x, kb.y);
        }
    }
    asm volatile("setmaxnreg.inc.sync.aligned.u32 168;");
    if (warp < 4) { bar_sync(6 + warp, 64); mbar_wait(sb + SB_UT + 8); }
    conv_core<NL, 16>(acc, sb, warp, kt, sb + SC_UT + warp * UT_STRIDE + 128, sb + SC_CT + lane * 16, warp * 288);
}

template <int ADD>
__device__ __forceinline__ void put_row(void* op, const uint32_t (&o)[4], uint32_t on) {
    if (ADD) asm volatile("{ .reg .pred p; setp.ne.u32 p, %5, 0; @p red.relaxed.gpu.global.add.noftz.v4.bf16x2 [%0], {%1, %2, %3, %4}; }"
                          :: "l"(op), "r"(o[0]), "r"(o[1]), "r"(o[2]), "r"(o[3]), "r"(on) : "memory");
    else asm volatile("{ .reg .pred p; setp.ne.u32 p, %5, 0; @p st.global.v4.b32 [%0], {%1, %2, %3, %4}; }" :: "l"(op), "r"(o[0]), "r"(o[1]), "r"(o[2]), "r"(o[3]), "r"(on) : "memory");
}

__device__ __forceinline__ void conv_low(int lane, const Params& p, uint32_t sb, int slab, int warp, uint32_t t0, uint4 (&x)[4]) {
    const uint32_t kt = sb + SH_KT + warp * KH_BYTES;
    mbar_wait(sb + FB_UT);
    if (lane < 11) sts128(kt + 16 * (lane < 4 ? lane : 128 + lane), 0, 0, 0, 0);
    __syncwarp();
    if (warp < 4) sleep_until<100>(t0 + KDELAY3);
#pragma unroll 1
    for (int c = warp;; c ^= 12) {
        kfetch<3>(lane, p, 16 * slab + c, lds32(sb + SF_TK), x);
        kstore(lane, x, kt, sb + SH_CT);
        x[1].w = 0;
        if (c < 8 && clk() - t0 >= (warp < 4 ? KDELAY4 : KDELAY2)) kissue<3>(lane, p, 16 * slab + (c ^ 12), x);
        __syncwarp();
        float acc[16][4];
        conv_core<0, NL>(acc, sb, warp, kt, sb + SH_UT + c * UH_STRIDE + 4 * (c & 8) + 128, sb + SH_CT + lane * 16, (c < 8 ? sb + SH_OUT + c * OH_STRIDE : kt + 32) + lane * 16);
        if (c >= 8) break;
    }
    __syncwarp();
    if (warp < 8 - NOUT) bar_arrive(13, 320);
}

__device__ __forceinline__ void mixed_output(int lane, const Params& p, uint32_t sb, int slab, int warp, bool dry) {
    const int t = lane & 3, mi = lane >> 3, r8 = lane & 7, h = warp & 1, q0 = (warp >> 1) & (NOUT / 2 - 1);
    if (warp >= 8 && !dry) {
        const uint32_t tag = lds32(sb + SF_TK), tg = tag << 14;
        const int i = 96 * h + lane;
        uint4 r[3];
        for (int it = 0;;) {
            uint32_t bad = 0;
#pragma unroll
            for (int k = 0; k < 3; k++) r[k] = ld_rlx128(&p.scr->rec[4 * i + 128 * k]);
            const uint32_t z = ld_acq32(&p.scr->zero[8 * (2 * slab + h)]);
#pragma unroll
            for (int k = 0; k < 3; k++) bad |= (r[k].x ^ tg) | (r[k].y ^ tg) | (r[k].z ^ tg) | (r[k].w ^ tg);
            if ((bad & 0xc000u) == 0 && z == tag) break;
            POLL_GUARD(it);
        }
        mbar_wait(sb + FB_GU);
#pragma unroll
        for (int k = 0; k < 3; k++) sts128(sb + SF_XS + 16 * i + 512 * k, r[k].x, r[k].y, r[k].z, r[k].w);
        __syncwarp();
        bar_arrive(13, 320);
        return;
    }
    int row = 32 * q0 + 8 * (lane & 2) + 8 * h + (lane >> 2);
    const int cl = 2 * mi + (r8 & 1);
    uint32_t ua = sb + SH_UT + cl * UH_STRIDE + ((r8 & 2) ? UH_HI : 0) + 128 + h * UH_PL + 16 * (r8 >> 2) + 32 * q0;
    uint32_t ya = sb + ((r8 & 2) ? SH_KT + 32 + (cl ^ 4) * KH_BYTES : SH_OUT + cl * OH_STRIDE) + h * 128 + 16 * (r8 >> 2) + 32 * q0;
    __nv_bfloat16* op = p.out + row * DM + 16 * slab + 8 * (t & 1);
    if (!dry) bar_sync(13, 320);
    const uint32_t thr = key_thr(lds32(sb + SF_SEL + 28));
#pragma unroll 1
    for (int q = 0; q < 8 / NOUT; q++, row += 16 * NOUT, ua += 16 * NOUT, ya += 16 * NOUT, op += 16 * NOUT * DM) {
        uint32_t r[NL], u[NL][4], y[NL][4], routed = 0;
#pragma unroll
        for (int i = 0; i < NL; i++) { r[i] = lds32(sb + SF_XS + 4 * row + 512 * i); ldsm4t(u[i], ua + 128 * i); ldsm4t(y[i], ya + 256 * i); }
#pragma unroll
        for (int i = 0; i < NL; i++) {
            const uint32_t gg = __byte_perm(r[i], 0, 0x1010) & 0x3fff3fffu;
            uint32_t om = hsub2(0x3f803f80u, gg);
            const bool add = ((r[i] & 0xffff0000u) | (uint32_t)(2047 - 128 * i - row)) >= thr;
            if (add) { om = 0; routed |= 1 << i; }
#pragma unroll
            for (int k = 0; k < 4; k++) y[i][k] = hfma2(gg, y[i][k], hmul2(om, u[i][k]));
            put_row<0>(op + 128 * i * DM, y[i], !(dry || add));
        }
        if (routed && !dry) {
#pragma unroll
            for (int i = 0; i < NL; i++) put_row<1>(op + 128 * i * DM, y[i], 1 & (routed >> i));
        }
        __syncwarp();
    }
}

__device__ __forceinline__ uint32_t utile_addr(uint32_t sb, int row, int c8) {
    return sb + SC_UTILE + (row >> 9) * 8192 + (((row >> 4) & 3) + 4 * (row & 1) + 8 * ((row >> 7) & 3) + 32 * ((row >> 1) & 7)) * 32 + ((c8 ^ row) & 1) * 16;
}

__device__ __forceinline__ void conv_helper(int lane, const Params& p, const CUtensorMap* mU, uint32_t sb, int cb, int hw, uint32_t t0) {
    const int g = lane >> 2, t = lane & 3, mi = lane >> 3, r8 = lane & 7;
    const int rank = cb & 1, slab = cb >> 1;
    const uint32_t bar_out = sb + SB_OUT;
    asm volatile("setmaxnreg.dec.sync.aligned.u32 88;");
    uint32_t tag = 0;
    if (elect()) {
        const uint32_t b = sb + SC_BAR + 8 * hw;
        mbar_init(b, hw < 4 ? 1 : 9); mbar_init(bar_out + 8 * hw, 1);
        mbar_fence_init();
        if (hw < 6) mbar_expect(b, hw == 4 ? 8192 + sizeof(Consts) : 8192);
        if (hw == 4) bulk_load(sb + SC_CT, p.consts, sizeof(Consts), b);
        if (hw < 4) {
            if (hw >= 2) spin_until(t0, VDELAY);
            tma5d(sb + SC_UTILE + hw * 8192, mU, 16 * slab, 4 * rank, 0, 4 * hw, 0, b);
        }
        mbar_expect(bar_out + 8 * hw, 4096);
        if (hw == 4) tag = take_ticket(&p.scr->launch);
    }
    __syncwarp();
    cluster_arrive_relaxed();
    if (lane < 16) sts128(sb + SC_UT + hw * UT_STRIDE + mi * UT_PL + r8 * 16, 0, 0, 0, 0);
    if (lane < 17) sts128(sb + SC_KT + hw * KT_BYTES + 16 * (lane < 4 ? lane : lane < 11 ? 128 + lane : 164 + lane), 0, 0, 0, 0);
    if (hw == 7) sts64(sb + SC_CT + 3584 + lane * 16, mapa(sb + SC_OUT + rank * OUT_HALF + g * 32 + (t & 1) * 16, t >> 1), mapa(bar_out, t >> 1));
    if (hw == 4) { tag = tag_of(__reduce_max_sync(0xffffffffu, tag)); sts32(sb + SC_TAG, tag); }
    cluster_wait();
    {
        const int box = hw >> 2, h = hw & 1, k0 = hw & 2;
        const uint32_t src = sb + SC_UTILE + box * 8192 + h * 4096 + k0 * 256 + (32 * mi + (r8 >> 1) + 4 * (r8 & 1)) * 32;
        const uint32_t so = ((rank ^ r8) & 1) << 4;
        const uint32_t dst = sb + SC_UT + g * UT_STRIDE + 128 + h * UT_PL + k0 * 128 + (32 * box + 4 * rank + t) * 16;
        const uint32_t rdst = mapa(dst, rank ^ 1), rbar = mapa(sb + SB_UT, rank ^ 1);
#pragma unroll 1
        for (int i = 0; i < 2; i++) {
            mbar_wait(sb + SC_BAR + 8 * box + 16 * i);
            const uint32_t ts = clk();
            uint32_t a[2][4], b[2][4];
#pragma unroll
            for (int k = 0; k < 2; k++) { ldsm4t(a[k], src + (so ^ 16) + k * 256 + i * 16384); ldsm4t(b[k], src + so + k * 256 + i * 16384); }
#pragma unroll
            for (int k = 0; k < 2; k++) sts128(dst + k * 128 + i * 1024, b[k][0], b[k][1], b[k][2], b[k][3]);
#pragma unroll
            for (int k = 0; k < 2; k++) {
                if (k == 0) { __syncwarp(); if (lane == 0) mbar_arrive(sb + SB_UT + 8 * i); }
                spin_until(ts, (hw + 8 * k) * PACE);
                st_async128(rdst + k * 128 + i * 1024, a[k][0], a[k][1], a[k][2], a[k][3], rbar + 8 * i);
            }
        }
    }
}

__device__ __forceinline__ void conv_output(int lane, const Params& p, uint32_t sb, int cb, int hw, uint32_t t0, bool dry) {
    const int g = lane >> 2, t = lane & 3, mi = lane >> 3, r8 = lane & 7;
    const int rank = cb & 1, slab = cb >> 1;
    const uint32_t bar_out = sb + SB_OUT, s_key = sb + SC_KEY;
    if (hw == 5) {
        uint32_t tn = t0 + WDELAY + 3 * WPER0 + 6 * WPER;
        sleep_until<300>(tn - 800);
        const int q = 72 * lane + cb, i = q / 120, r = q % 120, od = (i < 4 ? 4 * (r & ~3) + 4 * i + (r & 3) : q) * 4608;
#pragma unroll 1
        for (int n = 0; n < 8; n++, tn += DPER) {
            const int o = __shfl_sync(0xffffffffu, od, n);
            sleep_until<20>(tn);
            if (elect()) prefetch_l2(p.wd + o, 9216);
        }
        return;
    }
    if (hw == 4) {
        const uint32_t tag = lds32(sb + SC_TAG);
        uint32_t key;
        sleep_until<400>(t0 + SDELAY);
        for (int it = 0;;) {
            key = ld_rlx32(&p.scr->sel[g]);
            if (__all_sync(0xffffffffu, key >> 29 == tag)) break;
            POLL_GUARD(it);
            __nanosleep(200);
        }
        if (lane == 31) sts32(s_key, key);
        bar_arrive(1, 224);
        const int row = key_row(key);
        if (((row >> 6) & 1) == rank) asm volatile("st.relaxed.gpu.global.v2.b32 [%0], {%1, %1};" :: "l"(p.out + row * DM + 16 * slab + 4 * t), "r"(0) : "memory");
        __syncwarp();
        asm volatile("fence.acq_rel.gpu;" ::: "memory");
        if (lane < 8) st_rlx32(&p.scr->zero[8 * cb + lane], tag);
        bar_arrive(10, 224);
        return;
    }
    if (!dry) bar_sync(1, 224);
    const uint32_t last = lds32(s_key), tg = last >> 29 << 14;
    const int st = 2 + min(hw >> 1, 2), i0 = 4 * (hw & 1);
    const int row = 256 * st + 128 * (g >> 2) + 64 * rank + 32 * (t >> 1) + 16 * (g & 1) + 8 * ((g >> 1) & 1) + i0;
    uint4 r[2];
    r[0] = r[1] = make_uint4(tg, tg, tg, tg);
    for (int it = 0;;) {
        if (!dry) { r[0] = ld_rlx128(&p.scr->rec[row]); r[1] = ld_rlx128(&p.scr->rec[row + 768]); }
        if ((((r[0].x ^ tg) | (r[0].y ^ tg) | (r[0].z ^ tg) | (r[0].w ^ tg) | (r[1].x ^ tg) | (r[1].y ^ tg) | (r[1].z ^ tg) | (r[1].w ^ tg)) & 0xc000u) == 0) break;
        POLL_GUARD(it);
    }
    __syncwarp();
    const uint32_t thr = key_thr(last);
    const uint32_t ya = sb + SC_OUT + st * OUT_STAGE + ((r8 >> 1) & 1) * OUT_HALF + (2 * mi + (r8 & 1)) * 288 + (2 * i0 + (r8 >> 2)) * 16;
    __nv_bfloat16* const op = p.out + row * DM + 16 * slab + 8 * (t & 1);
    uint32_t gg[8], o[8][4], routed = 0;
#pragma unroll
    for (int k = 0; k < 2; k++) {
        const uint32_t rr[4] = {r[k].x, r[k].y, r[k].z, r[k].w}, ua = utile_addr(sb, row + 768 * k, t & 1);
#pragma unroll
        for (int i = 0; i < 4; i++) {
            const int n = 4 * k + i;
            gg[n] = __byte_perm(rr[i], 0, 0x1010) & 0x3fff3fffu;
            uint32_t om = hsub2(0x3f803f80u, gg[n]);
            if (((rr[i] & 0xffff0000u) | (uint32_t)(2047 - 768 * k - i - row)) >= thr) { om = 0; routed |= 1 << n; }
            const uint4 u4 = lds128((ua ^ ((i & 1) * 16)) + (i & 1) * 128 + (i >> 1) * 1024);
            o[n][0] = hmul2(om, u4.x); o[n][1] = hmul2(om, u4.y); o[n][2] = hmul2(om, u4.z); o[n][3] = hmul2(om, u4.w);
        }
    }
    const uint32_t on = dry ? 0 : row >= 128 * NL ? 0xff : 0xf0;
    if (!dry) bar_sync(10, 224);
#pragma unroll 1
    for (int once = blockIdx.y; once < 1; once++) {
#pragma unroll
        for (int k = 0; k < 2; k++) {
            if (!dry && 2 * st + 6 * k + 1 >= NL) mbar_wait(bar_out + 8 * st + 24 * k);
            uint32_t y[4][4];
#pragma unroll
            for (int i = 0; i < 4; i++) ldsm4t(y[i], ya + 3 * k * OUT_STAGE + 32 * i);
#pragma unroll
            for (int i = 0; i < 4; i++) {
#pragma unroll
                for (int e = 0; e < 4; e++) y[i][e] = hfma2(gg[4 * k + i], y[i][e], o[4 * k + i][e]);
                put_row<0>(op + (768 * k + i) * DM, y[i], on & ~routed & (1 << (4 * k + i)));
            }
            if (on & routed & (15 << 4 * k)) {
#pragma unroll
                for (int i = 0; i < 4; i++) put_row<1>(op + (768 * k + i) * DM, y[i], routed & (1 << (4 * k + i)));
            }
            __syncwarp();
        }
    }
}

struct Maps { const CUtensorMap *U2, *R, *G64, *Wd; };
struct WMaps { CUtensorMap m[4]; };

__device__ __forceinline__ void load_weights(const Params& p, const Maps& m, uint32_t sb, int f, bool pure, int n, int n1, uint32_t& tn) {
#pragma unroll 1
    for (; n < n1; n++) {
        const uint32_t b = sb + FB_W + 8 * n, d = sb + n * (pure ? PIECE_P : PIECE_H);
        if (n >= (pure ? 3 : 4)) mbar_wait(n < 4 ? sb + FB_SEL : n < 9 ? sb + FB_KG : n < 13 ? sb + FB_FREE : sb + FB_FREE + 8);
        sleep_until<30>(tn);
        tn += n < 3 ? WPER0 : n < 9 ? WPER : DPER * 5 / 3;
        __syncwarp();
        if (elect()) {
            mbar_expect(b, n >= 9 ? DPIECE : pure ? PIECE_P : PIECE_H);
            if (n == 9) mbar_arrive_peer(mapa(sb + FB_PEER, 1));
            if (n >= 9) tma3d(d - 9 * PIECE_P, m.Wd, 0, n < 13 ? 64 * f + 32 * n - 288 : 16 * f + 3840, 0, b);
            else {
#pragma unroll 1
                for (int i = pure ? 3 : 1; i >= 0; i--) tma2d(d + 4096 * (i + min(i, 2)), m.G64 + i, i < 2 ? 64 * f : 3840 + 16 * f, 64 * n, b);
            }
        }
    }
}

__device__ __forceinline__ void above(uint4 x, uint32_t m, uint32_t& a, uint32_t& b) {
    asm("{ .reg .u32 p, q, r, s; mad.lo.u32 p, %2, -1, %6; mad.lo.u32 q, %3, -1, %6; mad.lo.u32 r, %4, -1, %6; mad.lo.u32 s, %5, -1, %6;"
        "shr.u32 p, p, 31; shr.u32 q, q, 31; shr.u32 r, r, 31; shr.u32 s, s, 31; add.u32 %0, %0, p; add.u32 %1, %1, q; add.u32 %0, %0, r; add.u32 %1, %1, s; }"
        : "+r"(a), "+r"(b) : "r"(x.x), "r"(x.y), "r"(x.z), "r"(x.w), "r"(m));
}
__device__ __forceinline__ void select_rows(int lane, const Params& p, uint32_t sb, int f, int sw, uint32_t tag, uint32_t t0) {
    const int tid = 32 * sw + lane;
    uint4 k[6];
    uint32_t qm[6];
    const uint32_t ca = sb + SF_CNT + (lane & blockIdx.y);
    tag <<= 29;
    k[5] = make_uint4(tag, tag, tag, tag);
    sts128(sb + SF_LIST + tid * 16, 0, 0, 0, 0); sts128(sb + SF_LIST + 1536 + tid * 16, 0, 0, 0, 0); sts128(sb + SF_LIST + 2560 + tid * 16, 0, 0, 0, 0);
    sleep_until<40>(t0 + PDELAY);
    bool bad[6] = {true, true, true, true, true, sw == 0};
    for (int it = 0;;) {
#pragma unroll
        for (int i = 0; i < 6; i++) if (bad[i]) k[i] = ld_rlx128(&p.scr->rec[L_SEQ + 384 * i + 4 * tid]);
#pragma unroll
        for (int i = 0; i < 6; i++) {
            qm[i] = max(__vimax3_u32(k[i].x, k[i].y, k[i].z), k[i].w);
            bad[i] = ((min(__vimin3_u32(k[i].x, k[i].y, k[i].z), k[i].w) ^ tag) | (qm[i] ^ tag)) >= 0x20000000u;
        }
        if (!__any_sync(0xffffffffu, bad[0] | bad[1] | bad[2] | bad[3] | bad[4] | bad[5])) break;
        POLL_GUARD(it);
    }
    {
        uint32_t mx[6];
#pragma unroll
        for (int i = 0; i < 6; i++) mx[i] = __reduce_max_sync(0xffffffffu, qm[i]);
        sts128(sb + SF_MAX + 16 * sw, mx[0], mx[1], mx[2], mx[3]); sts32(sb + SF_MAX + 48 + 4 * sw, mx[4]);
        if (sw == 0) sts32(sb + SF_MAX + 60, mx[5]);
    }
    bar_sync(8, 96);
    uint32_t thr;
    {
        const uint32_t m = lds32(sb + SF_MAX + (lane & 15) * 4);
        const uint4 x = lds128(sb + SF_MAX + 2 * (lane & 16)), y = lds128(sb + SF_MAX + 2 * (lane & 16) + 16);
        uint32_t rk = 0, r2 = 0;
        above(x, m, rk, r2); above(y, m, rk, r2);
        rk += r2;
        thr = __reduce_max_sync(0xffffffffu, rk + __shfl_xor_sync(0xffffffffu, rk, 16) == 7 ? m : 0u);
    }
    uint32_t pos = 0;
    uint32_t cnt = (thr - 1 - qm[4]) >> 31, c2 = (thr - 1 - qm[5]) >> 31;
    above(make_uint4(qm[0], qm[1], qm[2], qm[3]), thr - 1, cnt, c2);
    cnt = 16 * (cnt + c2);
    asm volatile("{ .reg .pred p; setp.ne.u32 p, %2, 0; @p atom.shared.add.u32 %0, [%1], %2; }" : "+r"(pos) : "r"(ca), "r"(cnt) : "memory");
#pragma unroll
    for (int i = 0; i < 6; i++) if (qm[i] >= thr) { sts128(sb + SF_LIST + pos, k[i].x, k[i].y, k[i].z, k[i].w); pos += 16; }
    bar_sync(8, 96);
    const int n = lds32(sb + SF_CNT);
    uint32_t m, rk;
    int base = 0;
#pragma unroll 1
    do {
        m = lds32(sb + SF_LIST + base + 12 * (lane & 28) + 16 * sw + 4 * (lane & 3));
        rk = 0;
        uint32_t r2 = 0;
        int i = 0;
#pragma unroll 1
        do {
            uint4 x[6];
#pragma unroll
            for (int e = 0; e < 6; e++) x[e] = lds128(sb + SF_LIST + i + 16 * e);
#pragma unroll
            for (int e = 0; e < 6; e++) above(x[e], m, rk, r2);
        } while ((i += 16 * 6) < n);
        rk += r2;
        if (rk < 8) sts32(sb + SF_SEL + 4 * rk, m);
    } while ((base += 384) < n);
    if (RARE(n > 384)) {
        bar_sync(8, 96);
        rk = tid; m = lds32(sb + SF_SEL + 4 * (lane & 7));
    }
    if (rk < 8) {
        mbar_expect(sb + FB_X, 1152);
        bulk_load2(sb + SF_XS + 1168 * rk, p.u + key_row(m) * DM, 1152, sb + FB_X);
        st_async32(mapa(sb + SF_SEL + 4 * rk, 1), m, mapa(sb + FB_X, 1));
        if (f == 0) st_rlx32(&p.scr->sel[rk], m);
    }
    __syncwarp();
}

__device__ __forceinline__ bool ffn_worker(int lane, const Params& p, const Maps& m, uint32_t sb, int f, bool pure, int gw, uint32_t t0, uint32_t tag, uint32_t tn) {
    const int mi = lane >> 3, r8 = lane & 7, kr = 8 * (mi >> 1) + r8;
    const uint32_t sh = sb + (pure ? SP_H : SH_H);
    uint4* const pdst = p.scr->part + ((12 * (f & 1) + 2 * gw) * 30 + (f >> 1)) * 32 + lane;
    {
        const int piece = pure ? PIECE_P : PIECE_H;
        const uint32_t ws = gw < 8 ? 2048 : 1024, xa = sb + SF_XS + r8 * 1168 + mi * 16;
        const uint32_t wa = (gw < 8 ? sb + kr * 128 + ((gw ^ r8) << 4) : sb + 16384 + kr * 64 + (((gw ^ (r8 >> 1)) & 3) << 4)) + (mi & 1) * 4 * ws;
        uint32_t a[9][4][4];
        auto fetch = [&](int n) {
            mbar_wait(sb + FB_W + 8 * n);
#pragma unroll
            for (int s = 0; s < 4; s++) ldsm4t(a[n][s], wa + n * piece + s * ws);
        };
        auto release = [&](int n) {
            asm volatile("" :: "r"(a[n][0][0]), "r"(a[n][1][0]), "r"(a[n][2][0]), "r"(a[n][3][0]) : "memory");
            __syncwarp();
            if (lane == 0) mbar_arrive(sb + FB_FREE + 4 * (n - 3));
        };
        auto clear = [&]() { if (gw < 6) { st_pkt(pdst, 0, 0, 0, 0); st_pkt(pdst + 30 * 32, 0, 0, 0, 0); } };
        fetch(0); fetch(1); fetch(2); fetch(3); release(3);
        fetch(4); fetch(5); release(5);
        if (!pure && gw == 5) {
            mbar_wait(sb + FB_FREE + 8);
            sleep_until<30>(tn);
            __syncwarp();
            if (elect()) {
#pragma unroll 1
                for (int i = 0; i < (f < 48 ? 5 : 4); i++) {
                    mbar_expect(sb + FB_D + 8 * i, DPIECE);
                    tma3d(sb + i * DPIECE, m.Wd, 0, i < 4 ? 64 * (f & ~1) + 32 * i : 16 * f + 3824, 9 * (f & 1), sb + FB_D + 8 * i);
                }
            }
        }
        mbar_wait(sb + FB_X);
        float c[4][4] = {};
#pragma unroll
        for (int n = 0; n < 9; n++) {
            uint32_t x[2][4];
            ldsm4(x[0], xa + 128 * n); ldsm4(x[1], xa + 128 * n + 64);
            if (n >= 2 && n < 5) fetch(n + 4);
#pragma unroll
            for (int s = 0; s < 4; s++) mma_bf(c[s], a[n][s][0], a[n][s][1], a[n][s][2], a[n][s][3], x[s >> 1][2 * (s & 1)], x[s >> 1][2 * (s & 1) + 1]);
        }
        const float g0 = rbf((c[0][0] + c[1][0]) + (c[2][0] + c[3][0])), g1 = rbf((c[0][1] + c[1][1]) + (c[2][1] + c[3][1]));
        const float u0 = rbf((c[0][2] + c[1][2]) + (c[2][2] + c[3][2])), u1 = rbf((c[0][3] + c[1][3]) + (c[2][3] + c[3][3]));
        uint32_t hp = pack_bf16(rbf(g0 * sigmoidf_(g0)) * u0, rbf(g1 * sigmoidf_(g1)) * u1);
        asm volatile("movmatrix.sync.aligned.m8n8.trans.b16 %0, %0;" : "+r"(hp));
        const uint32_t ho = ((gw >> 1) + 4 * ((f & 1) | (gw >> 3))) * 256 + lane * 8 + (gw & 1) * 4;
        const bool pp = f < 48 && !pure;
        if (f < 48) mbar_wait(sb + (pure ? FB_FREE + 8 : FB_PEER));
        st_async32(mapa(sb + (pp ? SP_H : SH_H) + ho, ~f & 1), hp, mapa(sb + FB_GU, ~f & 1));
        sts32(sh + ho, hp);
        __syncwarp();
        if (lane == 0) mbar_arrive(sb + FB_GU);
        clear();
    }
    if (gw < 6) {
        uint32_t off[3], w[2][6][4];
#pragma unroll
        for (int k = 0; k < 3; k++) off[k] = sb + ((3 * gw + k) >> 1) * 2048 + kr * 64 + ((((2 * (gw + k) + (mi & 1)) ^ (r8 >> 1)) & 3) << 4);
        float d[6][4] = {};
        auto dfetch = [&](int i) {
            mbar_wait(sb + FB_D + 8 * i);
#pragma unroll
            for (int k = 0; k < 6; k++) ldsm4t(w[i & 1][k], off[k % 3] + k / 3 * 1024 + i * (pure ? PIECE_P : DPIECE));
        };
        uint2 hv[10];
        auto dmult = [&](int i) {
#pragma unroll
            for (int k = 0; k < 6; k++) mma_bf(d[k], w[i & 1][k][0], w[i & 1][k][1], w[i & 1][k][2], w[i & 1][k][3], hv[2 * i + k / 3].x, hv[2 * i + k / 3].y);
        };
        dfetch(0); dfetch(1);
        mbar_wait(sb + FB_GU);
#pragma unroll
        for (int i = 0; i < 10; i++) hv[i] = lds64(sh + lane * 8 + i * 256);
        dmult(0); dfetch(2); dmult(1); dfetch(3); dmult(2);
        if (f < 48) { dfetch(4); dmult(3); dmult(4); } else dmult(3);
        auto word = [&](int k) { return pack_bf16(d[k >> 1][2 * (k & 1)] + d[3 + (k >> 1)][2 * (k & 1)], d[k >> 1][2 * (k & 1) + 1] + d[3 + (k >> 1)][2 * (k & 1) + 1]); };
#pragma unroll
        for (int k = 0; k < 2; k++) st_pkt(pdst + k * 30 * 32, word(3 * k), word(3 * k + 1), word(3 * k + 2), tag);
        if (pure) bar_arrive(13, 384);
        return false;
    }
    return true;
}

__device__ __forceinline__ void ffn_gather(int lane, const Params& p, uint32_t sb, int idx, int gw) {
    const uint4* src = p.scr->part + (idx * 30 + 5 * gw - 30) * 32 + lane;
    uint4 v[5] = {};
#pragma unroll 1
    for (uint32_t tag = 0;;) {
        for (int it = 0; ((v[0].w ^ tag) | (v[1].w ^ tag) | (v[2].w ^ tag) | (v[3].w ^ tag) | (v[4].w ^ tag)) != 0;) {
#pragma unroll
            for (int k = 0; k < 5; k++) if (v[k].w != tag) v[k] = ld_pkt(src + k * 32);
            POLL_GUARD(it);
        }
        float s[6] = {};
#pragma unroll
        for (int k = 0; k < 5; k++) { s[0] += bf_lo(v[k].x); s[1] += bf_hi(v[k].x); s[2] += bf_lo(v[k].y); s[3] += bf_hi(v[k].y); s[4] += bf_lo(v[k].z); s[5] += bf_hi(v[k].z); }
#pragma unroll
        for (int k = 0; k < 3; k++) sts64(sb + SP_RED + gw * 768 + k * 256 + lane * 8, __float_as_uint(s[2 * k]), __float_as_uint(s[2 * k + 1]));
        __syncwarp();
        if (tag) break;
        tag = lds32(sb + SF_TK);
        bar_sync(13, 384);
        spin_until(clk(), GDELAY);
    }
    bar_arrive(12, 288);
}

__device__ __forceinline__ void ffn_final(int lane, const Params& p, uint32_t sb, int idx, int warp) {
    const int r8 = lane & 7, i = 32 * max(warp - 13, 0) + lane, col = 24 * idx + 2 * (i >> 3);
    const uint32_t tag = lds32(sb + SF_TK);
    mbar_wait(sb + FB_X);
    const uint32_t key = lds32(sb + SF_SEL + 4 * r8), x = lds32(sb + SF_XS + r8 * 1168 + 2 * col);
    const int row = key_row(key);
    uint32_t rc;
    for (int it = 0;;) { rc = ld_rlx32(&p.scr->rec[row]); if (((rc >> 14) & 3u) == tag) break; POLL_GUARD(it); }
    const float om = rbf(1.f - bf_lo(rc & 0x3fffu)), rs = rbf(sigmoidf_(key_val(key)));
    __syncwarp();
#pragma unroll 1
    for (int real = 0;; real = 1) {
        float y0 = 0.f, y1 = 0.f;
#pragma unroll
        for (int k = 6; k < 12; k++) {
            const uint32_t ra = sb + SP_RED + 768 * k + (i >> 3) * 64 + r8 * 4;
            y0 += __uint_as_float(lds32(ra)); y1 += __uint_as_float(lds32(ra + 32));
        }
        uint32_t o = pack_bf16(om * rbf(bf_lo(x) + rbf(rbf(y0) * rs)), om * rbf(bf_hi(x) + rbf(rbf(y1) * rs)));
        asm volatile("" : "+r"(o));
        if (real) { red_bf2(p.out + row * DM + col, o); break; }
        mbar_wait(sb + FB_GU);
        for (int it = 0; ld_acq32(&p.scr->zero[8 * (2 * (col >> 4) + ((row >> 6) & 1))]) != tag;) POLL_GUARD(it);
        __syncwarp();
        bar_sync(12, 288);
    }
}

__device__ __forceinline__ bool ffn_cta(int lane, const Params& p, const Maps& m, uint32_t sb, int f, bool pure, int idx, int warp, uint32_t t0, uint4 (&x)[4], int ch) {
    const int g = lane >> 2, t = lane & 3, mi = lane >> 3, r8 = lane & 7;
    const int nw = pure ? 12 : 8, ng = pure ? 3 : idx < 4 ? 6 : 5;
    uint32_t tag = 0, tn = t0 + WDELAY;
    if (warp == 13) {
        if (elect()) {
            mbar_init(sb + FB_WR, 1);
            mbar_fence_init();
            mbar_expect(sb + FB_WR, 2304);
            bulk_load(sb + SF_WR, p.wr, 1152, sb + FB_WR); bulk_load(sb + SF_WR + 1152, p.gatew, 1152, sb + FB_WR);
            mbar_init(sb + FB_TK, 1);
#pragma unroll
            for (int i = 0; i < 14; i++) mbar_init(sb + FB_W + 8 * i, 1);
            mbar_init(sb + FB_FREE, nw); mbar_init(sb + FB_FREE + 8, nw);
            mbar_init(sb + FB_SEL, ng); mbar_init(sb + FB_KG, nw + ng); mbar_init(sb + FB_UT, 4); mbar_init(sb + FB_GU, nw + 1); mbar_init(sb + FB_PEER, 1); mbar_init(sb + FB_X, (f & 1) ? 1 : 8);
            mbar_fence_init();
            mbar_expect(sb + FB_GU, f < 48 && !pure ? 1536 : 1024);
            if (f & 1) mbar_expect(sb + FB_X, 8 * 1156);
            prefetch_map(m.Wd);
        }
        __syncwarp();
        cluster_arrive_relaxed();
        load_weights(p, m, sb, f, pure, 0, pure ? 14 : 9, tn);
        if (pure) return false;
        mbar_wait(sb + FB_TK);
        tag = lds32(sb + SF_TK);
    } else if (warp >= nw) {
        const int r0 = pure ? 24 * idx : 576 + 40 * idx + 8 * min(idx, 4);
        const int grp = warp == 12 ? 0 : warp > 12 ? warp - 13 : warp - 5;
        const uint32_t rows = sb + (pure ? SP_R : grp < 5 ? SH_R : SH_R5 - 5 * 9216) + grp * 9216, bar_r = sb + FB_R + 8 * grp;
        if (elect()) {
            mbar_init(bar_r, 1); mbar_fence_init(); mbar_expect(bar_r, grp < 6 ? 9216 : NL * 4096 + sizeof(Consts));
            if (grp < ng) { spin_until(t0, RDELAY); tma3d(rows, m.R, 0, r0 + 8 * grp, 0, bar_r); }
        }
        __syncwarp();
        cluster_arrive_relaxed();
        if (grp == 0 && elect()) tag = take_ticket(&p.scr->launch);
        uint32_t* rp = &p.scr->rec[r0 + 8 * grp + g + L_SEQ * (t ^ 1)];
        uint32_t wa = sb + SF_WR + ((r8 >> 1) & 1) * 1152 + (2 * mi + (r8 & 1)) * 16, ra = rows + r8 * 128 + ((mi ^ r8) << 4), ts = t ? 14 : 29, kb = t ? 0 : 2047 - r0 - 8 * grp - g;
        asm volatile("" : "+l"(rp), "+r"(wa), "+r"(ra), "+r"(ts), "+r"(kb));
        if (grp < ng && t < 2) st_rlx32(rp, 0);
        if (f == 0 && grp == 2) st_rlx32(&p.scr->sel[lane], 0);
        if (grp == 6) {
            sleep_until<50>(t0 + HDELAY);
            if (elect()) { tma5d(sb + SH_RAW, m.U2, 16 * idx, 0, 0, 0, 0, bar_r); tma5d(sb + SH_RAW + NL * 2048, m.U2, 16 * idx, 4, 0, 0, 0, bar_r);
                bulk_load(sb + SH_CT, p.consts + sizeof(Consts), sizeof(Consts), bar_r); }
        }
        __syncwarp();
        cluster_wait();
        if (grp < ng) {
            mbar_wait(sb + FB_WR);
            uint32_t wv[9][4];
#pragma unroll
            for (int k = 0; k < 9; k++) ldsm4(wv[k], wa + 128 * k);
            float c[3][4];
            const uint32_t rb2 = ra ^ 64;
            if (grp == 0 && elect()) { sts64(sb + SF_CNT, 0, tag_of(tag)); mbar_arrive(sb + FB_TK); }
            __syncwarp();
            mbar_wait(bar_r);
#pragma unroll
            for (int k = 0; k < 18; k++) {
                uint32_t a[4];
                ldsm4(a, ((k & 1) ? rb2 : ra) + (k >> 1) * 1024);
                if (k < 3) mma_bf0(c[k], a[0], a[1], a[2], a[3], wv[k >> 1][2 * (k & 1)], wv[k >> 1][2 * (k & 1) + 1]);
                else mma_bf(c[k % 3], a[0], a[1], a[2], a[3], wv[k >> 1][2 * (k & 1)], wv[k >> 1][2 * (k & 1) + 1]);
            }
            mbar_wait(sb + FB_TK);
            tag = lds32(sb + SF_TK);
            kb |= tag << ts;
            const float s = (c[0][0] + c[0][3]) + (c[1][0] + c[1][3]) + (c[2][0] + c[2][3]);
            const uint32_t sr = pack_bf16(0.f, s), rb = sr ^ ((((int)sr >> 31) & 0x7fff0000u) | 0x80000000u);
            if (ts == 29) st_rlx32(rp, (rb >> 3) | kb);
            const uint32_t rec = __shfl_up_sync(0xffffffffu, rb, 1) | kb | (pack_bf16(sigmoidf_(bf_hi(sr)), 0.f) & 0x3fffu);
            if (t == 1) st_rlx32(rp, rec);
            if (lane == 0) { mbar_arrive(sb + FB_SEL); mbar_arrive(sb + FB_KG); }
        }
        if (warp >= 12) { if (!(f & 1)) select_rows(lane, p, sb, f, grp, tag, t0); }
        else {
            const int r = warp & 1, h = (warp >> 1) & 1;
            const uint32_t src = sb + SH_RAW + r * NL * 2048 + (8 * NL * (4 * h + mi) + (r8 >> 1) + 4 * (r8 & 1)) * 32 + (r8 & 1) * 16;
            const uint32_t dst = sb + SH_UT + g * UH_STRIDE + 128 + h * UH_PL + (4 * r + t) * 16;
            uint32_t a[2 * NL][4];
            mbar_wait(sb + FB_TK);
            tag = lds32(sb + SF_TK);
            mbar_wait(sb + FB_RAW);
#pragma unroll
            for (int k = 0; k < 2 * NL; k++) ldsm4t(a[k], (src ^ (16 * (k & 1))) + (k >> 1) * 256);
            mbar_wait(sb + FB_SEL);
#pragma unroll
            for (int k = 0; k < 2 * NL; k++) sts128(dst + (k & 1) * UH_HI + (k >> 1) * 128, a[k][0], a[k][1], a[k][2], a[k][3]);
            sts128(dst - 128, 0, 0, 0, 0); sts128(dst - 128 + UH_HI, 0, 0, 0, 0);
            __syncwarp();
            if (lane == 0) mbar_arrive(sb + FB_UT);
        }
    } else {
        mbar_wait(sb + FB_TK);
        tag = lds32(sb + SF_TK);
        if (warp < nw / 2) st_pkt(p.scr->kx + ch * 128 + 96 + lane, x[3].x, x[3].y, x[3].z, __byte_perm(x[3].w, tag, 0x5410));
        else kpublish(lane, p, ch, tag, x);
        if (!pure) { conv_low(lane, p, sb, idx, warp, t0, x); return warp >= 8 - NOUT; }
    }
    if (pure && warp >= 12) return true;
    return ffn_worker(lane, p, m, sb, f, pure, pure ? warp : warp - 8, t0, tag, tn);
}

__global__ void __cluster_dims__(2, 1, 1) __launch_bounds__(NTHR, 1)
fused_kernel(const Params p, const __grid_constant__ CUtensorMap mU, const __grid_constant__ CUtensorMap mU2, const __grid_constant__ CUtensorMap mR,
             const __grid_constant__ WMaps mW, const __grid_constant__ CUtensorMap mWd) {
    extern __shared__ __align__(1024) uint8_t smem_raw[];
    const uint32_t sb = smem_u32(smem_raw);
    const uint32_t t0 = __shfl_sync(0xffffffffu, clk(), 0);
    const int bx = blockIdx.x;
    const int f = bx - FFN0, cb = bx < FFN0 ? bx : bx - NFFN;
    const bool ffn = (unsigned)f < NFFN, pure = (unsigned)f < 48 && !(f & 1);
    const int idx = !ffn ? cb >> 1 : max(f >> 1, f - 24), nch = pure ? 6 : 4, c0 = nch * idx, co = !ffn ? 8 * (bx & 1) : pure ? 12 : 4;
    const int warp = warp_id(), lane = lane_id();
    KParams kp;
    {
        const int w = threadIdx.x >> 5, h = w >= nch, c = c0 + w - nch * h;
        if (w < 2 * nch) kp = kload(p, 4 * (c & ~3) + co + (c & 3), h);
    }
    const int half = warp >= nch, j = warp - nch * half, ch = 4 * ((c0 + j) & ~3) + co + ((c0 + j) & 3);
    [&]() {
    uint32_t q[8][4];
    uint4 x[4];
    if (warp < 2 * nch) {
        const uint32_t stage = sb + (!ffn ? SC_STG : pure ? SP_STG : SH_STG), mine = stage + warp * KG_STAGE, other = stage + (half ? j : warp + nch) * KG_STAGE;
        float kv[21], fin;
        cluster_arrive_relaxed();
        kgen(lane, kp, mine, kv, fin, sb);
        ksend(lane, kv, fin, mine, half);
        if (!ffn) bar_arrive(half ? 11 + j : 2 + j, 64);
        if (ffn || half) {
            bar_sync(2 + j, 64);
            if (half) {
                krecv(lane, kv, fin, other, 0, 0); krecv(lane, kv, fin, other, 1, 4); krecv(lane, kv, fin, other, 2, 8); krecv(lane, kv, fin, other, 3, 12);
                kv[16] = kv[16] * fin + __uint_as_float(lds32(other + 2048)) + bf_lo(kp.dskip);
            } else krecv(lane, kv, fin, other, 0, 17);
            if (ffn) { __syncwarp(); if (lane == 0) mbar_arrive(sb + FB_KG); }
            if (half) kpack(lane, kv, x);
            else { x[3] = kwords8(lane, kv); x[0] = x[1] = x[2] = make_uint4(0, 0, 0, 0); }
            if (!ffn) {
                mbar_wait(sb + SB_UT);
                const uint32_t tag = lds32(sb + SC_TAG);
                kpublish(lane, p, ch, tag, x);
                kstore(lane, x, sb + SC_KT + j * KT_BYTES, sb + SC_CT);
                bar_arrive(6 + j, 64);
                conv_windows(lane, sb, warp, q);
                mbar_wait(sb + SB_UT + 8);
                sleep_until<100>(t0 + ((bx & 1) ? KDELAY1 : KDELAY0));
                x[1].w = 0;
                kfetch<4>(lane, p, ch + 4, tag, x);
                kstore(lane, x, sb + SC_KT + warp * KT_BYTES, sb + SC_CT);
                x[3].w = __byte_perm(x[3].w, x[3].z, 0x5410);
            }
        }
        if (!ffn) {
            if (!half) {
            mbar_wait(sb + SB_UT);
            conv_windows(lane, sb, warp, q);
                bar_sync(11 + j, 64);
                krecv(lane, kv, fin, other, 0, 17);
                x[3] = kwords8(lane, kv);
            }
            conv_warp(lane_id(), sb, warp, q, x[3]);
            return;
        }
    }
    int more = 0;
    if (ffn) { const Maps m = {&mU2, &mR, mW.m, &mWd}; more = ffn_cta(lane, p, m, sb, f, pure, idx, warp, t0, x, ch); }
    else { conv_helper(lane, p, &mU, sb, cb, warp - 8, t0); more = 1; }
    if (__shfl_sync(0xffffffffu, more, 0)) {
        const int lane = lane_id();
        if (!ffn || (pure && warp == 15)) conv_output(lane, p, sb, ffn ? 0 : cb, warp - 8, t0, ffn);
        else if (!pure || warp == 14) mixed_output(lane, p, sb, idx, warp, pure);
        else if (warp < 12) ffn_gather(lane, p, sb, idx, warp);
        if (pure && warp >= 12) ffn_final(lane, p, sb, idx, warp);
    }
    }();
}

typedef CUresult (*EncodeFn)(CUtensorMap*, CUtensorMapDataType, cuuint32_t, void*, const cuuint64_t*, const cuuint64_t*, const cuuint32_t*, const cuuint32_t*,
                             CUtensorMapInterleave, CUtensorMapSwizzle, CUtensorMapL2promotion, CUtensorMapFloatOOBfill);

CUtensorMap make_map(EncodeFn fn, const void* base, uint64_t inner, uint64_t outer, uint32_t bi, uint32_t bo, CUtensorMapSwizzle sw,
                     CUtensorMapL2promotion pr = CU_TENSOR_MAP_L2_PROMOTION_NONE) {
    CUtensorMap m;
    cuuint64_t dims[2] = {inner, outer};
    cuuint64_t strides[1] = {inner * 2};
    cuuint32_t box[2] = {bi, bo};
    cuuint32_t es[2] = {1, 1};
    fn(&m, CU_TENSOR_MAP_DATA_TYPE_BFLOAT16, 2, (void*)base, dims, strides, box, es, CU_TENSOR_MAP_INTERLEAVE_NONE, sw, pr, CU_TENSOR_MAP_FLOAT_OOB_FILL_NONE);
    return m;
}

}

extern "C" void kernel_launch(void* const* d_in, const int* in_sizes, int n_in, void* d_out, int out_size) {
    (void)in_sizes; (void)n_in; (void)out_size;
    static EncodeFn fn = nullptr;
    static Scratch* scr = nullptr;
    static char* consts = nullptr;
    if (!fn) {
        void* ptr = nullptr; cudaDriverEntryPointQueryResult qr;
        cudaGetDriverEntryPoint("cuTensorMapEncodeTiled", &ptr, cudaEnableDefault, &qr);
        fn = (EncodeFn)ptr;
        cudaGetSymbolAddress((void**)&scr, g_scr);
        cudaGetSymbolAddress((void**)&consts, g_consts);
        cudaFuncSetAttribute(fused_kernel, cudaFuncAttributeMaxDynamicSharedMemorySize, SMEM_BYTES);
    }
    typedef const __nv_bfloat16* bp;
    Params p;
    p.u = (bp)d_in[0]; p.Are = (bp)d_in[1]; p.Aim = (bp)d_in[2]; p.Bre = (bp)d_in[3]; p.Bim = (bp)d_in[4]; p.Cre = (bp)d_in[5]; p.Cim = (bp)d_in[6];
    p.logdt = (bp)d_in[7]; p.Dskip = (bp)d_in[8]; p.wr = (bp)d_in[10]; p.gatew = (bp)d_in[14]; p.wd = (bp)d_in[13];
    p.out = (__nv_bfloat16*)d_out; p.scr = scr; p.consts = consts;
    CUtensorMap mU, mU2;
    {
        cuuint64_t dims[5] = {DM, 8, 2, L_SEQ / 128, 8};
        cuuint64_t strides[4] = {16 * DM * 2, DM * 2, 128 * DM * 2, 2 * DM * 2};
        cuuint32_t box[5] = {16, 4, 2, 4, 8};
        cuuint32_t es[5] = {1, 1, 1, 1, 1};
        fn(&mU, CU_TENSOR_MAP_DATA_TYPE_BFLOAT16, 5, d_in[0], dims, strides, box, es, CU_TENSOR_MAP_INTERLEAVE_NONE, CU_TENSOR_MAP_SWIZZLE_32B,
           CU_TENSOR_MAP_L2_PROMOTION_NONE, CU_TENSOR_MAP_FLOAT_OOB_FILL_NONE);
        box[3] = NL;
        fn(&mU2, CU_TENSOR_MAP_DATA_TYPE_BFLOAT16, 5, d_in[0], dims, strides, box, es, CU_TENSOR_MAP_INTERLEAVE_NONE, CU_TENSOR_MAP_SWIZZLE_32B,
           CU_TENSOR_MAP_L2_PROMOTION_NONE, CU_TENSOR_MAP_FLOAT_OOB_FILL_NONE);
    }
    CUtensorMap mR, mWd;
    {
        cuuint64_t dims[3] = {64, L_SEQ, 9};
        cuuint64_t strides[2] = {DM * 2, 128};
        cuuint32_t box[3] = {64, 8, 9};
        cuuint32_t es[3] = {1, 1, 1};
        fn(&mR, CU_TENSOR_MAP_DATA_TYPE_BFLOAT16, 3, d_in[0], dims, strides, box, es, CU_TENSOR_MAP_INTERLEAVE_NONE, CU_TENSOR_MAP_SWIZZLE_128B,
           CU_TENSOR_MAP_L2_PROMOTION_NONE, CU_TENSOR_MAP_FLOAT_OOB_FILL_NONE);
        dims[0] = 32; dims[1] = FF; dims[2] = 18; strides[1] = 64; box[0] = box[1] = 32;
        fn(&mWd, CU_TENSOR_MAP_DATA_TYPE_BFLOAT16, 3, d_in[13], dims, strides, box, es, CU_TENSOR_MAP_INTERLEAVE_NONE, CU_TENSOR_MAP_SWIZZLE_64B,
           CU_TENSOR_MAP_L2_PROMOTION_L2_128B, CU_TENSOR_MAP_FLOAT_OOB_FILL_NONE);
    }
    WMaps mW;
    mW.m[0] = make_map(fn, d_in[11], FF, DM, 64, 64, CU_TENSOR_MAP_SWIZZLE_128B);
    mW.m[1] = make_map(fn, d_in[12], FF, DM, 64, 64, CU_TENSOR_MAP_SWIZZLE_128B);
    mW.m[2] = make_map(fn, d_in[11], FF, DM, 32, 64, CU_TENSOR_MAP_SWIZZLE_64B, CU_TENSOR_MAP_L2_PROMOTION_L2_128B);
    mW.m[3] = make_map(fn, d_in[12], FF, DM, 32, 64, CU_TENSOR_MAP_SWIZZLE_64B, CU_TENSOR_MAP_L2_PROMOTION_L2_128B);
    fused_kernel<<<NCTA, NTHR, SMEM_BYTES>>>(p, mU, mU2, mR, mW, mWd);
}
```
